```python
import torch

def _softmax(x, axis=-1):
    return torch.softmax(x, dim=axis)
def _gelu(x):
    return torch.nn.functional.gelu(x, approximate="tanh")
def _silu(x):
    return torch.nn.functional.silu(x)
def _sigmoid(x):
    return torch.sigmoid(x)
def _layernorm(x, axis=-1, eps=1e-5):
    m = x.mean(dim=axis, keepdim=True)
    v = x.var(dim=axis, keepdim=True, unbiased=False)
    return (x - m) / torch.sqrt(v + eps)
def _scatter_add(tgt, idx, src, axis=0):
    return tgt.clone().index_add_(axis, idx, src)
def _segment_sum(src, seg, n):
    out = torch.zeros((n,) + src.shape[1:], dtype=src.dtype)
    return out.index_add_(0, seg, src)
def _pad(x, pw):
    flat = tuple(v for pair in reversed(pw) for v in pair)
    return torch.nn.functional.pad(x, flat)

kernel_name = 'gated_mix__gqa_block_cached__mixer_channel_mlp__decode'

def setup_inputs():

    _w = (lambda a: (lambda t: t.to(torch.bfloat16) if t.is_floating_point() else t)(torch.as_tensor(a)))
    def _A_setup():
        B, Sq, D = 4, 1, 1024
        Hq, Hkv, Sk, Dh = 32, 4, 8192, 128
        assert Hq % Hkv == 0, (Hq, Hkv)
        return {
            "x": _w((lambda *s: torch.randn(*s, dtype=torch.bfloat16) * 0.05)(B, Sq, D)),
            "k_cache": _w((lambda *s: torch.randn(*s, dtype=torch.bfloat16) * 6.4)(B, Hkv, Sk, Dh)),
            "v_cache": _w((lambda *s: torch.randn(*s, dtype=torch.bfloat16) * 0.4)(B, Hkv, Sk, Dh)),
            "wq": _w((lambda *s: torch.randn(*s, dtype=torch.bfloat16) * 6.4)(D, Hq * Dh) * (D ** -0.5)),
            "wo": _w((lambda *s: torch.randn(*s, dtype=torch.bfloat16) * 0.4)(Hq * Dh, D) * ((Hq * Dh) ** -0.5)),
        }
    _A_in = _A_setup()

    def _B_setup():
        B, S, D, F = 4, 1, 1024, 3584
        return {
            "x": _w((lambda *s: torch.randn(*s, dtype=torch.bfloat16) * 0.05)(B, S, D)),
            "w1": _w((lambda *s: torch.randn(*s, dtype=torch.bfloat16) * 0.8)(D, F) * (D ** -0.5)),
            "b1": _w((lambda *s: torch.randn(*s, dtype=torch.bfloat16) * 0.4)(F)),
            "w2": _w((lambda *s: torch.randn(*s, dtype=torch.bfloat16) * 0.05)(F, D) * (F ** -0.5)),
            "b2": _w((lambda *s: torch.randn(*s, dtype=torch.bfloat16) * 0.05)(D)),
        }
    _B_in = _B_setup()

    return {
        "A_x": _A_in["x"],
        "A_k_cache": _A_in["k_cache"],
        "A_v_cache": _A_in["v_cache"],
        "A_wq": _A_in["wq"],
        "A_wo": _A_in["wo"],
        "B_x": _B_in["x"],
        "B_w1": _B_in["w1"],
        "B_b1": _B_in["b1"],
        "B_w2": _B_in["w2"],
        "B_b2": _B_in["b2"],
        "gate_w": _w((lambda *s: torch.randn(*s, dtype=torch.bfloat16) * 0.05)(1024) * 16.0),
    }

def reference(A_x, A_k_cache, A_v_cache, A_wq, A_wo, B_x, B_w1, B_b1, B_w2, B_b2, gate_w):
    def _A_ref(x, k_cache, v_cache, wq, wo):
        B, Sq, D = x.shape
        Hq, Dh = 32, 128
        Hkv = k_cache.shape[1]
        rep = Hq // Hkv
        q = (lambda x, *d: x.permute(*d))((x @ wq).reshape(B, Sq, Hq, Dh), 0, 2, 1, 3)
        k = (lambda x, n, axis: torch.repeat_interleave(x, n, dim=axis))(k_cache, rep, axis=1)
        v = (lambda x, n, axis: torch.repeat_interleave(x, n, dim=axis))(v_cache, rep, axis=1)
        scores = torch.einsum("bhqd,bhkd->bhqk", q, k) * (Dh ** -0.5)
        p = _softmax(scores, axis=-1)
        o = torch.einsum("bhqk,bhkd->bhqd", p, v)
        return (lambda x, *d: x.permute(*d))(o, 0, 2, 1, 3).reshape(B, Sq, Hq * Dh) @ wo

    def _B_ref(x, w1, b1, w2, b2):
        y = _layernorm(x, axis=-1)
        h = _gelu(torch.einsum("bsd,df->bsf", y, w1) + b1)
        return torch.einsum("bsf,fd->bsd", h, w2) + b2

    x = A_x
    g = _sigmoid((x * gate_w).sum(-1, keepdims=True))
    a = _A_ref(x, A_k_cache, A_v_cache, A_wq, A_wo)
    b = _B_ref(x, B_w1, B_b1, B_w2, B_b2)
    return g * a + (1 - g) * b
```

```cpp
#include <cuda_runtime.h>
#include <cuda.h>
#include <cuda_bf16.h>
#include <stdint.h>

namespace {

constexpr int NCTA = 128;
constexpr int NTHREADS = 320;
constexpr int NSTAGE = 12;
constexpr int STAGE_BYTES = 16384;

constexpr int D_MODEL = 1024;
constexpr int F_DIM = 3584;
constexpr int SK = 8192;

constexpr int SM_P = NSTAGE * STAGE_BYTES;
constexpr int SM_XS = SM_P;
constexpr int SM_YS = SM_P + 4160;
constexpr int SM_QS = SM_P + 16384;
constexpr int SM_HS = SM_QS + 2176;
constexpr int SM_RED = SM_HS + 3648;
constexpr int SM_MX = SM_RED + 2048;
constexpr int SM_LS = SM_MX + 256;
constexpr int SM_BAR = SM_LS + 256;
constexpr int SM_FLAG = SM_BAR + 2 * NSTAGE * 8;
constexpr int SM_TOTAL = SM_FLAG + 16;
constexpr int SM_ALLOC = SM_TOTAL + 1024;

constexpr int XS_STRIDE = 520 * 2;
constexpr int HS_STRIDE = 456 * 2;
constexpr int QS_STRIDE = 136 * 2;

constexpr int BAR_INIT = 0;
constexpr int BAR_CONS = 1;
constexpr int BAR_PAIR = 2;
constexpr int BAR_KV = 6;
constexpr int BAR_HS = 7;
constexpr int BAR_O = 8;
constexpr int BAR_B = 9;
constexpr int BAR_A = 10;

struct TMaps {
    CUtensorMap wq, w1, k, v, w2, wo;
};

__device__ __align__(256) unsigned int g_epoch[NCTA];
__device__ __align__(256) unsigned long long g_qbuf[2 * 4 * 4096];
__device__ __align__(256) unsigned long long g_hbuf[2 * F_DIM * 4];
__device__ __align__(256) unsigned long long g_obuf1[NCTA * 8 * 128];
__device__ __align__(256) unsigned long long g_ml[NCTA * 8 * 2];
__device__ __align__(256) unsigned long long g_obuf2[4 * 32 * 64];
__device__ __align__(256) unsigned long long g_abuf[NCTA * 16 * 32];
__device__ __align__(256) unsigned long long g_bbuf[NCTA * 16 * 32];

__device__ __forceinline__ uint32_t smem_u32(const void* p) { return (uint32_t)__cvta_generic_to_shared(p); }

__device__ __forceinline__ void mbar_init(uint32_t bar, uint32_t cnt) {
    asm volatile("mbarrier.init.shared::cta.b64 [%0], %1;" ::"r"(bar), "r"(cnt) : "memory");
}
__device__ __forceinline__ void mbar_expect_tx(uint32_t bar, uint32_t bytes) {
    asm volatile("mbarrier.arrive.expect_tx.shared::cta.b64 _, [%0], %1;" ::"r"(bar), "r"(bytes) : "memory");
}
__device__ __forceinline__ void mbar_arrive_cnt(uint32_t bar, uint32_t cnt) {
    asm volatile("mbarrier.arrive.shared::cta.b64 _, [%0], %1;" ::"r"(bar), "r"(cnt) : "memory");
}
__device__ __forceinline__ bool mbar_try(uint32_t bar, uint32_t parity) {
    uint32_t ok;
    asm volatile(
        "{\n.reg .pred p;\n"
        "mbarrier.try_wait.parity.shared::cta.b64 p, [%1], %2;\n"
        "selp.u32 %0, 1, 0, p;\n}\n"
        : "=r"(ok)
        : "r"(bar), "r"(parity)
        : "memory");
    return ok != 0;
}
__device__ __noinline__ void mbar_wait_slow(uint32_t bar, uint32_t parity, volatile uint32_t* flag) {
    long long t0 = clock64();
    for (uint32_t it = 0; it < 0x40000000u; it++) {
        if (mbar_try(bar, parity)) return;
        if ((it & 63u) == 63u) {
            if (*flag) return;
            if (clock64() - t0 > 2000000000LL) { *flag = 1u; return; }
        }
    }
}
__device__ __forceinline__ void mbar_wait(uint32_t bar, uint32_t parity, volatile uint32_t* flag) {
    if (mbar_try(bar, parity)) return;
    if (mbar_try(bar, parity)) return;
    mbar_wait_slow(bar, parity, flag);
}

__device__ __forceinline__ void tma_2d(uint32_t dst, const CUtensorMap* tm, int c0, int c1, uint32_t bar) {
    asm volatile(
        "cp.async.bulk.tensor.2d.shared::cluster.global.mbarrier::complete_tx::bytes [%0], [%1, {%3, %4}], [%2];"
        ::"r"(dst), "l"(tm), "r"(bar), "r"(c0), "r"(c1)
        : "memory");
}
__device__ __forceinline__ void bar_sync(int id, int cnt) { asm volatile("bar.sync %0, %1;" ::"r"(id), "r"(cnt) : "memory"); }
__device__ __forceinline__ void bar_arrive(int id, int cnt) { asm volatile("bar.arrive %0, %1;" ::"r"(id), "r"(cnt) : "memory"); }

__device__ __forceinline__ void ldsm_x4(uint32_t (&r)[4], uint32_t addr) {
    asm volatile("ldmatrix.sync.aligned.m8n8.x4.shared.b16 {%0,%1,%2,%3}, [%4];"
                 : "=r"(r[0]), "=r"(r[1]), "=r"(r[2]), "=r"(r[3])
                 : "r"(addr)
                 : "memory");
}
__device__ __forceinline__ void ldsm_x4_t(uint32_t (&r)[4], uint32_t addr) {
    asm volatile("ldmatrix.sync.aligned.m8n8.x4.trans.shared.b16 {%0,%1,%2,%3}, [%4];"
                 : "=r"(r[0]), "=r"(r[1]), "=r"(r[2]), "=r"(r[3])
                 : "r"(addr)
                 : "memory");
}
__device__ __forceinline__ void mma16816(float (&c)[4], const uint32_t (&a)[4], uint32_t b0, uint32_t b1) {
    asm volatile(
        "mma.sync.aligned.m16n8k16.row.col.f32.bf16.bf16.f32 {%0,%1,%2,%3}, {%4,%5,%6,%7}, {%8,%9}, {%0,%1,%2,%3};"
        : "+f"(c[0]), "+f"(c[1]), "+f"(c[2]), "+f"(c[3])
        : "r"(a[0]), "r"(a[1]), "r"(a[2]), "r"(a[3]), "r"(b0), "r"(b1));
}
__device__ __forceinline__ uint32_t lds32(uint32_t addr) {
    uint32_t v;
    asm volatile("ld.shared.b32 %0, [%1];" : "=r"(v) : "r"(addr) : "memory");
    return v;
}
__device__ __forceinline__ void sts32(uint32_t addr, uint32_t v) {
    asm volatile("st.shared.b32 [%0], %1;" ::"r"(addr), "r"(v) : "memory");
}

__device__ __forceinline__ float bf16r(float x) { return __bfloat162float(__float2bfloat16_rn(x)); }
__device__ __forceinline__ uint32_t pack_bf16(float lo, float hi) {
    __nv_bfloat162 v = __floats2bfloat162_rn(lo, hi);
    return *reinterpret_cast<uint32_t*>(&v);
}
__device__ __forceinline__ float bf_lo(uint32_t u) { return __uint_as_float(u << 16); }
__device__ __forceinline__ float bf_hi(uint32_t u) { return __uint_as_float(u & 0xffff0000u); }

__device__ __forceinline__ void ll_st1(unsigned long long* p, uint32_t d, uint32_t tag) {
    asm volatile("{\n.reg .b64 a;\nmov.b64 a, {%1, %2};\nst.relaxed.gpu.global.b64 [%0], a;\n}\n" ::"l"(p), "r"(d), "r"(tag) : "memory");
}
__device__ __forceinline__ void ll_st2(unsigned long long* p, uint32_t d0, uint32_t d1, uint32_t tag) {
    asm volatile(
        "{\n.reg .b64 a, b;\nmov.b64 a, {%1, %3};\nmov.b64 b, {%2, %3};\nst.relaxed.gpu.global.v2.b64 [%0], {a, b};\n}\n"
        ::"l"(p), "r"(d0), "r"(d1), "r"(tag)
        : "memory");
}
__device__ __forceinline__ bool ll_ld1(const unsigned long long* p, uint32_t& d, uint32_t tag) {
    uint32_t t;
    asm volatile("{\n.reg .b64 a;\nld.relaxed.gpu.global.b64 a, [%2];\nmov.b64 {%0, %1}, a;\n}\n" : "=r"(d), "=r"(t) : "l"(p) : "memory");
    return t == tag;
}
__device__ __forceinline__ bool ll_ld2(const unsigned long long* p, uint32_t& d0, uint32_t& d1, uint32_t tag) {
    uint32_t t0, t1;
    asm volatile(
        "{\n.reg .b64 a, b;\nld.relaxed.gpu.global.v2.b64 {a, b}, [%4];\nmov.b64 {%0, %1}, a;\nmov.b64 {%2, %3}, b;\n}\n"
        : "=r"(d0), "=r"(t0), "=r"(d1), "=r"(t1)
        : "l"(p)
        : "memory");
    return (t0 == tag) & (t1 == tag);
}
constexpr uint32_t POLL_LIMIT = 1u << 21;

template <int NKS>
__device__ __forceinline__ void gemv_tile(float (&acc0)[4], float (&acc1)[4], uint32_t a_addr, uint32_t b_addr, bool bvalid) {
    uint32_t a[NKS][4];
    uint32_t b[NKS][2];
#pragma unroll
    for (int ks = 0; ks < NKS; ks++) ldsm_x4_t(a[ks], a_addr + ks * 2048);
#pragma unroll
    for (int ks = 0; ks < NKS; ks++) {
        b[ks][0] = bvalid ? lds32(b_addr + ks * 32) : 0u;
        b[ks][1] = bvalid ? lds32(b_addr + ks * 32 + 16) : 0u;
    }
#pragma unroll
    for (int ks = 0; ks < NKS; ks++) {
        if (ks & 1) mma16816(acc1, a[ks], b[ks][0], b[ks][1]);
        else mma16816(acc0, a[ks], b[ks][0], b[ks][1]);
    }
}

__global__ void __launch_bounds__(NTHREADS, 1)
fused_kernel(const __grid_constant__ TMaps maps,
             const __nv_bfloat16* __restrict__ x, const __nv_bfloat16* __restrict__ b1,
             const __nv_bfloat16* __restrict__ b2, const __nv_bfloat16* __restrict__ gate_w,
             __nv_bfloat16* __restrict__ out) {
    extern __shared__ unsigned char smem_raw[];
    const uint32_t sbase = (smem_u32(smem_raw) + 1023u) & ~1023u;
    unsigned char* sptr = smem_raw + (sbase - smem_u32(smem_raw));
    volatile uint32_t* flag = reinterpret_cast<volatile uint32_t*>(sptr + SM_FLAG);

    const int c = blockIdx.x;
    const int tid = threadIdx.x;
    const int warp = tid >> 5;
    const int lane = tid & 31;
    const bool has_w1 = c < 112;
    const int n_pre = has_w1 ? 8 : 4;
    const int n_tiles = n_pre + 40;
    const uint32_t bar_full = sbase + SM_BAR;
    const uint32_t bar_empty = sbase + SM_BAR + NSTAGE * 8;

    if (warp == 8) {
        if (lane == 0) {
            for (int i = 0; i < NSTAGE; i++) {
                mbar_init(bar_full + i * 8, 1);
                mbar_init(bar_empty + i * 8, 8);
            }
            *flag = 0u;
            asm volatile("fence.mbarrier_init.release.cluster;" ::: "memory");
            asm volatile("fence.proxy.async.shared::cta;" ::: "memory");
        }
        __syncwarp();
        bar_arrive(BAR_INIT, 288);
        const int kv_row0 = (c >> 3) * SK + (c & 7) * 1024;
        int stage = 0;
        uint32_t ph = 1;
        for (int i = 0; i < n_tiles; i++) {
            if (lane == 0) {
                if (i >= NSTAGE) mbar_wait(bar_empty + stage * 8, ph, flag);
                const uint32_t dst = sbase + stage * STAGE_BYTES;
                const uint32_t fb = bar_full + stage * 8;
                int j = i;
                if (j < 4) {
                    mbar_expect_tx(fb, STAGE_BYTES);
                    tma_2d(dst, &maps.wq, (c >> 1) * 64, (c & 1) * 512 + j * 128, fb);
                } else if (j < n_pre) {
                    mbar_expect_tx(fb, STAGE_BYTES);
                    tma_2d(dst, &maps.w1, (c >> 1) * 64, (c & 1) * 512 + (j - 4) * 128, fb);
                } else {
                    j -= n_pre;
                    if (j < 32) {
                        const CUtensorMap* tm = j < 16 ? &maps.k : &maps.v;
                        const int row = kv_row0 + (j & 15) * 64;
                        mbar_expect_tx(fb, STAGE_BYTES);
                        tma_2d(dst, tm, 0, row, fb);
                        tma_2d(dst + 8192, tm, 64, row, fb);
                    } else if (j < 36) {
                        mbar_expect_tx(fb, 112 * 128);
                        tma_2d(dst, &maps.w2, (c >> 3) * 64, (c & 7) * 448 + (j - 32) * 112, fb);
                    } else {
                        mbar_expect_tx(fb, STAGE_BYTES);
                        tma_2d(dst, &maps.wo, (c >> 3) * 64, (c & 7) * 512 + (j - 36) * 128, fb);
                    }
                }
            }
            if (++stage == NSTAGE) { stage = 0; ph ^= 1u; }
        }
        return;
    }

    const uint32_t tag = *reinterpret_cast<volatile unsigned int*>(&g_epoch[c]) + 1u;
    const int g = lane >> 2;
    const int t = lane & 3;

    if (warp == 9) {
        float gate;
        {
            float z[4];
            uint4 gw[4];
#pragma unroll
            for (int i = 0; i < 4; i++) gw[i] = __ldg(reinterpret_cast<const uint4*>(gate_w) + i * 32 + lane);
#pragma unroll
            for (int b = 0; b < 4; b++) {
                float s = 0.f;
#pragma unroll
                for (int i = 0; i < 4; i++) {
                    uint4 xv = __ldg(reinterpret_cast<const uint4*>(x + b * D_MODEL) + i * 32 + lane);
                    const uint32_t xa[4] = {xv.x, xv.y, xv.z, xv.w};
                    const uint32_t wa[4] = {gw[i].x, gw[i].y, gw[i].z, gw[i].w};
#pragma unroll
                    for (int e = 0; e < 4; e++) {
                        s += bf16r(bf_lo(xa[e]) * bf_lo(wa[e]));
                        s += bf16r(bf_hi(xa[e]) * bf_hi(wa[e]));
                    }
                }
#pragma unroll
                for (int o = 16; o > 0; o >>= 1) s += __shfl_xor_sync(0xffffffffu, s, o);
                z[b] = s;
            }
            float zz = t == 0 ? z[0] : (t == 1 ? z[1] : (t == 2 ? z[2] : z[3]));
            zz = bf16r(zz);
            gate = bf16r(1.0f / (1.0f + __expf(-zz)));
        }
        const int ocol = (c >> 3) * 64 + (c & 7) * 8 + g;
        const float b2v = __bfloat162float(b2[ocol]);

        bar_sync(BAR_KV, 288);
        {
            const int col0 = (c & 7) * 448;
            for (int u0 = 0; u0 < 896; u0 += 128) {
                uint32_t d[4][4];
                for (uint32_t it = 0; it < POLL_LIMIT; it++) {
                    bool ok = true;
#pragma unroll
                    for (int i = 0; i < 4; i++) {
                        const int u = u0 + i * 32 + lane;
                        const unsigned long long* p = g_hbuf + (size_t)col0 * 4 + u * 2;
                        ok &= ll_ld2(p, d[i][0], d[i][1], tag);
                        ok &= ll_ld2(p + F_DIM * 4, d[i][2], d[i][3], tag);
                    }
                    if (__all_sync(0xffffffffu, ok)) break;
                    __nanosleep(100);
                }
#pragma unroll
                for (int i = 0; i < 4; i++) {
                    const int u = u0 + i * 32 + lane;
                    const int cl = u >> 1;
                    const int bb = (u & 1) * 2;
                    const float bias = __bfloat162float(b1[col0 + cl]);
#pragma unroll
                    for (int e = 0; e < 2; e++) {
                        float v = bf16r(__uint_as_float(d[i][e]) + __uint_as_float(d[i][2 + e]));
                        v = bf16r(v + bias);
                        const float inner = 0.7978845608028654f * (v + 0.044715f * v * v * v);
                        const float hv = 0.5f * v * (1.0f + tanhf(inner));
                        *reinterpret_cast<__nv_bfloat16*>(sptr + SM_HS + (bb + e) * HS_STRIDE + cl * 2) = __float2bfloat16_rn(hv);
                    }
                }
            }
        }
        bar_arrive(BAR_HS, 288);

        bar_sync(BAR_O, 288);
        {
            const int p = c >> 3, r = c & 7;
            float f;
            {
                uint32_t mu = 0, lu = 0;
                const unsigned long long* pm = g_ml + ((size_t)(p * 8 + (lane & 7)) * 8 + r) * 2;
                for (uint32_t it = 0; it < POLL_LIMIT; it++) {
                    bool ok = ll_ld2(pm, mu, lu, tag);
                    if (__all_sync(0xffffffffu, ok)) break;
                    __nanosleep(50);
                }
                const float m = __uint_as_float(mu), l = __uint_as_float(lu);
                float M = m;
#pragma unroll
                for (int o = 4; o > 0; o >>= 1) M = fmaxf(M, __shfl_xor_sync(0xffffffffu, M, o));
                const float w = exp2f((m - M) * 1.4426950408889634f);
                float L = w * l;
#pragma unroll
                for (int o = 4; o > 0; o >>= 1) L += __shfl_xor_sync(0xffffffffu, L, o);
                f = w / L;
            }
            uint32_t d[8][4];
            for (uint32_t it = 0; it < POLL_LIMIT; it++) {
                bool ok = true;
#pragma unroll
                for (int s = 0; s < 8; s++) {
                    const unsigned long long* po = g_obuf1 + ((size_t)(p * 8 + s) * 8 + r) * 128 + lane * 4;
                    ok &= ll_ld2(po, d[s][0], d[s][1], tag);
                    ok &= ll_ld2(po + 2, d[s][2], d[s][3], tag);
                }
                if (__all_sync(0xffffffffu, ok)) break;
            }
            float o0 = 0.f, o1 = 0.f, o2 = 0.f, o3 = 0.f;
#pragma unroll
            for (int s = 0; s < 8; s++) {
                const float fs = __shfl_sync(0xffffffffu, f, s);
                o0 = fmaf(fs, __uint_as_float(d[s][0]), o0);
                o1 = fmaf(fs, __uint_as_float(d[s][1]), o1);
                o2 = fmaf(fs, __uint_as_float(d[s][2]), o2);
                o3 = fmaf(fs, __uint_as_float(d[s][3]), o3);
            }
            const int b = p >> 2, head = (p & 3) * 8 + r;
            ll_st2(g_obuf2 + ((size_t)(b * 32 + head) * 32 + lane) * 2, pack_bf16(o0, o2), pack_bf16(o1, o3), tag);
        }

        bar_sync(BAR_B, 288);
        float bterm;
        {
            uint32_t d[16];
            const unsigned long long* pb = g_bbuf + (size_t)c * 512 + lane;
            for (uint32_t it = 0; it < POLL_LIMIT; it++) {
                bool ok = true;
#pragma unroll
                for (int s = 0; s < 16; s++) ok &= ll_ld1(pb + s * 32, d[s], tag);
                if (__all_sync(0xffffffffu, ok)) break;
                __nanosleep(50);
            }
            float s0 = 0.f, s1 = 0.f;
#pragma unroll
            for (int s = 0; s < 16; s += 2) { s0 += __uint_as_float(d[s]); s1 += __uint_as_float(d[s + 1]); }
            float bv = bf16r(bf16r(s0 + s1) + b2v);
            bterm = bf16r(bf16r(1.0f - gate) * bv);
        }
        bar_sync(BAR_A, 288);
        {
            uint32_t d[16];
            const unsigned long long* pa = g_abuf + (size_t)c * 512 + lane;
            for (uint32_t it = 0; it < POLL_LIMIT; it++) {
                bool ok = true;
#pragma unroll
                for (int s = 0; s < 16; s++) ok &= ll_ld1(pa + s * 32, d[s], tag);
                if (__all_sync(0xffffffffu, ok)) break;
            }
            float s0 = 0.f, s1 = 0.f;
#pragma unroll
            for (int s = 0; s < 16; s += 2) { s0 += __uint_as_float(d[s]); s1 += __uint_as_float(d[s + 1]); }
            const float av = bf16r(s0 + s1);
            const float res = bf16r(gate * av) + bterm;
            out[t * D_MODEL + ocol] = __float2bfloat16_rn(res);
        }
        if (lane == 0) *reinterpret_cast<volatile unsigned int*>(&g_epoch[c]) = tag;
        return;
    }

    const int mt = warp & 3;
    const int kh2 = warp >> 2;
    const int khalf = c & 1;

    if (warp < 4) {
        uint4 xv[4];
#pragma unroll
        for (int i = 0; i < 4; i++) xv[i] = __ldg(reinterpret_cast<const uint4*>(x + warp * D_MODEL) + i * 32 + lane);
        float s = 0.f;
#pragma unroll
        for (int i = 0; i < 4; i++) {
            const uint32_t xa[4] = {xv[i].x, xv[i].y, xv[i].z, xv[i].w};
#pragma unroll
            for (int e = 0; e < 4; e++) s += bf_lo(xa[e]) + bf_hi(xa[e]);
        }
#pragma unroll
        for (int o = 16; o > 0; o >>= 1) s += __shfl_xor_sync(0xffffffffu, s, o);
        const float mean = s * (1.0f / 1024.0f);
        float q = 0.f;
#pragma unroll
        for (int i = 0; i < 4; i++) {
            const uint32_t xa[4] = {xv[i].x, xv[i].y, xv[i].z, xv[i].w};
#pragma unroll
            for (int e = 0; e < 4; e++) {
                const float d0 = bf_lo(xa[e]) - mean, d1 = bf_hi(xa[e]) - mean;
                q += d0 * d0 + d1 * d1;
            }
        }
#pragma unroll
        for (int o = 16; o > 0; o >>= 1) q += __shfl_xor_sync(0xffffffffu, q, o);
        const float mb = bf16r(mean);
        const float vb = bf16r(q * (1.0f / 1024.0f));
        const float den = bf16r(sqrtf(bf16r(vb + 1e-5f)));
#pragma unroll
        for (int i = 0; i < 2; i++) {
            const uint4 xs = khalf ? xv[2 + i] : xv[i];
            const uint32_t xa[4] = {xs.x, xs.y, xs.z, xs.w};
            uint32_t ya[4];
#pragma unroll
            for (int e = 0; e < 4; e++) {
                const float y0 = bf16r(bf_lo(xa[e]) - mb) / den;
                const float y1 = bf16r(bf_hi(xa[e]) - mb) / den;
                ya[e] = pack_bf16(y0, y1);
            }
            *reinterpret_cast<uint4*>(sptr + SM_XS + warp * XS_STRIDE + (i * 256 + lane * 8) * 2) = xs;
            *reinterpret_cast<uint4*>(sptr + SM_YS + warp * XS_STRIDE + (i * 256 + lane * 8) * 2) = make_uint4(ya[0], ya[1], ya[2], ya[3]);
        }
    }
    bar_sync(BAR_INIT, 288);

    int stage = 0;
    uint32_t ph = 0;
    const uint32_t l8 = lane & 7;
    const uint32_t offT = (l8 + 8 * (lane >> 4)) * 128 + ((((uint32_t)(2 * mt + ((lane >> 3) & 1))) ^ l8) << 4);
    const bool bvalid = g < 4;

    {
        float acc0[4] = {0.f, 0.f, 0.f, 0.f}, acc1[4] = {0.f, 0.f, 0.f, 0.f};
        const uint32_t baddr = sbase + SM_XS + (g & 3) * XS_STRIDE + (kh2 * 64 + 2 * t) * 2;
#pragma unroll 1
        for (int j = 0; j < 4; j++) {
            mbar_wait(bar_full + stage * 8, ph, flag);
            gemv_tile<4>(acc0, acc1, sbase + stage * STAGE_BYTES + kh2 * 8192 + offT, baddr + j * 256, bvalid);
            __syncwarp();
            if (lane == 0) mbar_arrive_cnt(bar_empty + stage * 8, 1);
            if (++stage == NSTAGE) { stage = 0; ph ^= 1u; }
        }
        float4* red = reinterpret_cast<float4*>(sptr + SM_RED) + mt * 16 + (g * 2 + (t & 1));
        if (kh2 == 1 && t < 2) *red = make_float4(acc0[0] + acc1[0], acc0[1] + acc1[1], acc0[2] + acc1[2], acc0[3] + acc1[3]);
        bar_sync(BAR_PAIR + mt, 64);
        if (kh2 == 0 && t < 2) {
            const float4 o = *red;
            const int col = (c >> 1) * 64 + mt * 16 + g;
            unsigned long long* p = g_qbuf + (size_t)(khalf * 4 + 2 * t) * 4096 + col;
            ll_st1(p, __float_as_uint(acc0[0] + acc1[0] + o.x), tag);
            ll_st1(p + 4096, __float_as_uint(acc0[1] + acc1[1] + o.y), tag);
            ll_st1(p + 8, __float_as_uint(acc0[2] + acc1[2] + o.z), tag);
            ll_st1(p + 4096 + 8, __float_as_uint(acc0[3] + acc1[3] + o.w), tag);
        }
    }
    if (has_w1) {
        float acc0[4] = {0.f, 0.f, 0.f, 0.f}, acc1[4] = {0.f, 0.f, 0.f, 0.f};
        const uint32_t baddr = sbase + SM_YS + (g & 3) * XS_STRIDE + (kh2 * 64 + 2 * t) * 2;
#pragma unroll 1
        for (int j = 0; j < 4; j++) {
            mbar_wait(bar_full + stage * 8, ph, flag);
            gemv_tile<4>(acc0, acc1, sbase + stage * STAGE_BYTES + kh2 * 8192 + offT, baddr + j * 256, bvalid);
            __syncwarp();
            if (lane == 0) mbar_arrive_cnt(bar_empty + stage * 8, 1);
            if (++stage == NSTAGE) { stage = 0; ph ^= 1u; }
        }
        float4* red = reinterpret_cast<float4*>(sptr + SM_RED + 1024) + mt * 16 + (g * 2 + (t & 1));
        if (kh2 == 1 && t < 2) *red = make_float4(acc0[0] + acc1[0], acc0[1] + acc1[1], acc0[2] + acc1[2], acc0[3] + acc1[3]);
        bar_sync(BAR_PAIR + mt, 64);
        if (kh2 == 0 && t < 2) {
            const float4 o = *red;
            const int col = (c >> 1) * 64 + mt * 16 + g;
            unsigned long long* p = g_hbuf + ((size_t)khalf * F_DIM + col) * 4 + 2 * t;
            ll_st2(p, __float_as_uint(acc0[0] + acc1[0] + o.x), __float_as_uint(acc0[1] + acc1[1] + o.y), tag);
            ll_st2(p + 32, __float_as_uint(acc0[2] + acc1[2] + o.z), __float_as_uint(acc0[3] + acc1[3] + o.w), tag);
        }
    }
    const int pair = c >> 3;
    uint32_t qf[8][2];
    {
        const int b = pair >> 2, hkv = pair & 3;
        const unsigned long long* p = g_qbuf + (size_t)b * 4096 + hkv * 1024 + tid * 4;
        uint32_t d[8];
        for (uint32_t it = 0; it < POLL_LIMIT; it++) {
            bool ok = ll_ld2(p, d[0], d[1], tag);
            ok &= ll_ld2(p + 2, d[2], d[3], tag);
            ok &= ll_ld2(p + 4 * 4096, d[4], d[5], tag);
            ok &= ll_ld2(p + 4 * 4096 + 2, d[6], d[7], tag);
            if (__all_sync(0xffffffffu, ok)) break;
            __nanosleep(100);
        }
        const uint32_t q01 = pack_bf16(__uint_as_float(d[0]) + __uint_as_float(d[4]), __uint_as_float(d[1]) + __uint_as_float(d[5]));
        const uint32_t q23 = pack_bf16(__uint_as_float(d[2]) + __uint_as_float(d[6]), __uint_as_float(d[3]) + __uint_as_float(d[7]));
        *reinterpret_cast<uint2*>(sptr + SM_QS + warp * QS_STRIDE + lane * 8) = make_uint2(q01, q23);
        bar_sync(BAR_CONS, 256);
#pragma unroll
        for (int i = 0; i < 4; i++) {
            uint32_t r[4];
            ldsm_x4(r, sbase + SM_QS + l8 * QS_STRIDE + (i * 4 + (lane >> 3)) * 16);
            qf[2 * i][0] = r[0]; qf[2 * i][1] = r[1];
            qf[2 * i + 1][0] = r[2]; qf[2 * i + 1][1] = r[3];
        }
    }
    float sc[8][4];
    {
        int st = stage + kh2;
        uint32_t php = ph;
        if (st >= NSTAGE) { st -= NSTAGE; php ^= 1u; }
        const uint32_t krow = mt * 16 + l8 + 8 * ((lane >> 3) & 1);
        const uint32_t khi = lane >> 4;
#pragma unroll
        for (int i = 0; i < 8; i++) {
            mbar_wait(bar_full + st * 8, php, flag);
            const uint32_t base = sbase + st * STAGE_BYTES + krow * 128;
            float c0[4] = {0.f, 0.f, 0.f, 0.f}, c1[4] = {0.f, 0.f, 0.f, 0.f};
            uint32_t a[8][4];
#pragma unroll
            for (int ks = 0; ks < 8; ks++)
                ldsm_x4(a[ks], base + (ks >> 2) * 8192 + (((uint32_t)((ks & 3) * 2) + khi) ^ l8) * 16);
#pragma unroll
            for (int ks = 0; ks < 8; ks++) {
                if (ks & 1) mma16816(c1, a[ks], qf[ks][0], qf[ks][1]);
                else mma16816(c0, a[ks], qf[ks][0], qf[ks][1]);
            }
            __syncwarp();
            if (lane == 0) mbar_arrive_cnt(bar_empty + st * 8, 2);
#pragma unroll
            for (int e = 0; e < 4; e++) sc[i][e] = bf16r(bf16r(c0[e] + c1[e]) * 0.08838834764831845f);
            st += 2;
            if (st >= NSTAGE) { st -= NSTAGE; php ^= 1u; }
        }
        stage += 16 - NSTAGE;
        ph ^= 1u;
        if (stage >= NSTAGE) { stage -= NSTAGE; ph ^= 1u; }
    }
    {
        float m0 = sc[0][0], m1 = sc[0][1];
#pragma unroll
        for (int i = 0; i < 8; i++) {
            m0 = fmaxf(m0, fmaxf(sc[i][0], sc[i][2]));
            m1 = fmaxf(m1, fmaxf(sc[i][1], sc[i][3]));
        }
#pragma unroll
        for (int o = 4; o < 32; o <<= 1) {
            m0 = fmaxf(m0, __shfl_xor_sync(0xffffffffu, m0, o));
            m1 = fmaxf(m1, __shfl_xor_sync(0xffffffffu, m1, o));
        }
        float2* mx = reinterpret_cast<float2*>(sptr + SM_MX);
        if (g == 0) mx[warp * 4 + t] = make_float2(m0, m1);
        bar_sync(BAR_CONS, 256);
        bar_arrive(BAR_KV, 288);
#pragma unroll
        for (int w = 0; w < 8; w++) {
            const float2 v = mx[w * 4 + t];
            m0 = fmaxf(m0, v.x);
            m1 = fmaxf(m1, v.y);
        }
        float l0 = 0.f, l1 = 0.f;
#pragma unroll
        for (int i = 0; i < 8; i++) {
            const float e0 = exp2f((sc[i][0] - m0) * 1.4426950408889634f);
            const float e1 = exp2f((sc[i][1] - m1) * 1.4426950408889634f);
            const float e2 = exp2f((sc[i][2] - m0) * 1.4426950408889634f);
            const float e3 = exp2f((sc[i][3] - m1) * 1.4426950408889634f);
            l0 += e0 + e2;
            l1 += e1 + e3;
            const uint32_t key = (2 * i + kh2) * 64 + mt * 16 + g;
            sts32(sbase + SM_P + key * 16 + t * 4, pack_bf16(e0, e1));
            sts32(sbase + SM_P + (key + 8) * 16 + t * 4, pack_bf16(e2, e3));
        }
#pragma unroll
        for (int o = 4; o < 32; o <<= 1) {
            l0 += __shfl_xor_sync(0xffffffffu, l0, o);
            l1 += __shfl_xor_sync(0xffffffffu, l1, o);
        }
        float2* ls = reinterpret_cast<float2*>(sptr + SM_LS);
        if (g == 0) ls[warp * 4 + t] = make_float2(l0, l1);
        bar_sync(BAR_CONS, 256);
        if (warp == 0 && g == 0) {
            float a0 = 0.f, a1 = 0.f;
#pragma unroll
            for (int w = 0; w < 8; w++) {
                const float2 v = ls[w * 4 + t];
                a0 += v.x;
                a1 += v.y;
            }
            unsigned long long* p = g_ml + ((size_t)c * 8 + 2 * t) * 2;
            ll_st2(p, __float_as_uint(m0), __float_as_uint(a0), tag);
            ll_st2(p + 2, __float_as_uint(m1), __float_as_uint(a1), tag);
        }
    }
    {
        float acc0[4] = {0.f, 0.f, 0.f, 0.f}, acc1[4] = {0.f, 0.f, 0.f, 0.f};
        const uint32_t paddr = sbase + SM_P + lane * 16;
#pragma unroll 1
        for (int j = 0; j < 16; j++) {
            uint32_t pb[2][4];
            ldsm_x4_t(pb[0], paddr + j * 1024);
            ldsm_x4_t(pb[1], paddr + j * 1024 + 512);
            mbar_wait(bar_full + stage * 8, ph, flag);
            const uint32_t base = sbase + stage * STAGE_BYTES + kh2 * 8192 + offT;
            uint32_t a[4][4];
#pragma unroll
            for (int ks = 0; ks < 4; ks++) ldsm_x4_t(a[ks], base + ks * 2048);
            mma16816(acc0, a[0], pb[0][0], pb[0][1]);
            mma16816(acc1, a[1], pb[0][2], pb[0][3]);
            mma16816(acc0, a[2], pb[1][0], pb[1][1]);
            mma16816(acc1, a[3], pb[1][2], pb[1][3]);
            __syncwarp();
            if (lane == 0) mbar_arrive_cnt(bar_empty + stage * 8, 1);
            if (++stage == NSTAGE) { stage = 0; ph ^= 1u; }
        }
        unsigned long long* p = g_obuf1 + ((size_t)c * 8 + 2 * t) * 128 + (warp * 8 + g) * 2;
        ll_st2(p, __float_as_uint(acc0[0] + acc1[0]), __float_as_uint(acc0[2] + acc1[2]), tag);
        ll_st2(p + 128, __float_as_uint(acc0[1] + acc1[1]), __float_as_uint(acc0[3] + acc1[3]), tag);
        bar_arrive(BAR_O, 288);
    }
    const int kr = c & 7;
    const size_t dst_off = ((size_t)((c & ~7) + 2 * mt) * 16 + (kr * 2 + kh2)) * 32 + g * 4 + 2 * t;
    {
        bar_sync(BAR_HS, 288);
        float acc0[4] = {0.f, 0.f, 0.f, 0.f}, acc1[4] = {0.f, 0.f, 0.f, 0.f};
        const uint32_t baddr = sbase + SM_HS + (g & 3) * HS_STRIDE + (kh2 * 64 + 2 * t) * 2;
#pragma unroll 1
        for (int j = 0; j < 4; j++) {
            mbar_wait(bar_full + stage * 8, ph, flag);
            const uint32_t aaddr = sbase + stage * STAGE_BYTES + kh2 * 8192 + offT;
            if (kh2 == 0) gemv_tile<4>(acc0, acc1, aaddr, baddr + j * 224, bvalid);
            else gemv_tile<3>(acc0, acc1, aaddr, baddr + j * 224, bvalid);
            __syncwarp();
            if (lane == 0) mbar_arrive_cnt(bar_empty + stage * 8, 1);
            if (++stage == NSTAGE) { stage = 0; ph ^= 1u; }
        }
        if (t < 2) {
            unsigned long long* p = g_bbuf + dst_off;
            ll_st2(p, __float_as_uint(acc0[0] + acc1[0]), __float_as_uint(acc0[1] + acc1[1]), tag);
            ll_st2(p + 512, __float_as_uint(acc0[2] + acc1[2]), __float_as_uint(acc0[3] + acc1[3]), tag);
        }
        bar_arrive(BAR_B, 288);
    }
    {
        uint32_t of[4][4][2];
        {
            const unsigned long long* p = g_obuf2 + ((size_t)((g & 3) * 32 + kr * 4) * 32 + kh2 * 16 + t) * 2;
            for (uint32_t it = 0; it < POLL_LIMIT; it++) {
                bool ok = true;
                if (bvalid) {
#pragma unroll
                    for (int j = 0; j < 4; j++)
#pragma unroll
                        for (int ks = 0; ks < 4; ks++) ok &= ll_ld2(p + (j * 32 + ks * 4) * 2, of[j][ks][0], of[j][ks][1], tag);
                }
                if (__all_sync(0xffffffffu, ok)) break;
                __nanosleep(50);
            }
            if (!bvalid) {
#pragma unroll
                for (int j = 0; j < 4; j++)
#pragma unroll
                    for (int ks = 0; ks < 4; ks++) of[j][ks][0] = of[j][ks][1] = 0u;
            }
        }
        float acc0[4] = {0.f, 0.f, 0.f, 0.f}, acc1[4] = {0.f, 0.f, 0.f, 0.f};
#pragma unroll
        for (int j = 0; j < 4; j++) {
            mbar_wait(bar_full + stage * 8, ph, flag);
            if (j == 3) bar_arrive(BAR_A, 288);
            const uint32_t base = sbase + stage * STAGE_BYTES + kh2 * 8192 + offT;
            uint32_t a[4][4];
#pragma unroll
            for (int ks = 0; ks < 4; ks++) ldsm_x4_t(a[ks], base + ks * 2048);
            mma16816(acc0, a[0], of[j][0][0], of[j][0][1]);
            mma16816(acc1, a[1], of[j][1][0], of[j][1][1]);
            mma16816(acc0, a[2], of[j][2][0], of[j][2][1]);
            mma16816(acc1, a[3], of[j][3][0], of[j][3][1]);
            if (++stage == NSTAGE) { stage = 0; ph ^= 1u; }
        }
        if (t < 2) {
            unsigned long long* p = g_abuf + dst_off;
            ll_st2(p, __float_as_uint(acc0[0] + acc1[0]), __float_as_uint(acc0[1] + acc1[1]), tag);
            ll_st2(p + 512, __float_as_uint(acc0[2] + acc1[2]), __float_as_uint(acc0[3] + acc1[3]), tag);
        }
    }
}

typedef CUresult (*EncodeFn)(CUtensorMap*, CUtensorMapDataType, cuuint32_t, void*, const cuuint64_t*, const cuuint64_t*,
                             const cuuint32_t*, const cuuint32_t*, CUtensorMapInterleave, CUtensorMapSwizzle,
                             CUtensorMapL2promotion, CUtensorMapFloatOOBfill);

void make_2d(EncodeFn enc, CUtensorMap* tm, void* base, uint64_t cols, uint64_t rows, uint32_t box_rows) {
    cuuint64_t gd[2] = {cols, rows};
    cuuint64_t gs[1] = {cols * 2};
    cuuint32_t bd[2] = {64, box_rows};
    cuuint32_t es[2] = {1, 1};
    enc(tm, CU_TENSOR_MAP_DATA_TYPE_BFLOAT16, 2, base, gd, gs, bd, es, CU_TENSOR_MAP_INTERLEAVE_NONE,
        CU_TENSOR_MAP_SWIZZLE_128B, CU_TENSOR_MAP_L2_PROMOTION_L2_128B, CU_TENSOR_MAP_FLOAT_OOB_FILL_NONE);
}

}

extern "C" void kernel_launch(void* const* d_in, const int* in_sizes, int n_in, void* d_out, int out_size) {
    (void)in_sizes; (void)n_in; (void)out_size;
    static TMaps maps;
    static void* cached[6] = {nullptr, nullptr, nullptr, nullptr, nullptr, nullptr};
    static EncodeFn enc = nullptr;
    if (!enc) {
        void* fn = nullptr;
        cudaDriverEntryPointQueryResult qr;
        cudaGetDriverEntryPoint("cuTensorMapEncodeTiled", &fn, cudaEnableDefault, &qr);
        enc = (EncodeFn)fn;
        cudaFuncSetAttribute(fused_kernel, cudaFuncAttributeMaxDynamicSharedMemorySize, SM_ALLOC);
    }
    void* cur[6] = {d_in[3], d_in[6], d_in[1], d_in[2], d_in[8], d_in[4]};
    bool same = true;
    for (int i = 0; i < 6; i++) same = same && (cur[i] == cached[i]);
    if (!same) {
        make_2d(enc, &maps.wq, d_in[3], 4096, 1024, 128);
        make_2d(enc, &maps.w1, d_in[6], F_DIM, 1024, 128);
        make_2d(enc, &maps.k, d_in[1], 128, 16 * SK, 64);
        make_2d(enc, &maps.v, d_in[2], 128, 16 * SK, 64);
        make_2d(enc, &maps.w2, d_in[8], 1024, F_DIM, 112);
        make_2d(enc, &maps.wo, d_in[4], 1024, 4096, 128);
        for (int i = 0; i < 6; i++) cached[i] = cur[i];
    }
    fused_kernel<<<NCTA, NTHREADS, SM_ALLOC, cudaStreamPerThread>>>(
        maps, (const __nv_bfloat16*)d_in[0], (const __nv_bfloat16*)d_in[7], (const __nv_bfloat16*)d_in[9],
        (const __nv_bfloat16*)d_in[10], (__nv_bfloat16*)d_out);
}
```

```cpp
#include <cuda_runtime.h>
#include <cuda.h>
#include <cuda_bf16.h>
#include <stdint.h>

namespace {

constexpr int NCTA = 128;
constexpr int NTHREADS = 384;
constexpr int NSTAGE = 12;
constexpr int STAGE_BYTES = 16384;

constexpr int D_MODEL = 1024;
constexpr int F_DIM = 3584;
constexpr int SK = 8192;

constexpr int SM_P = NSTAGE * STAGE_BYTES;
constexpr int SM_XS = SM_P;
constexpr int SM_GW = SM_P + 8256;
constexpr int SM_YS = SM_P + 16384;
constexpr int SM_B1 = SM_YS + 4160;
constexpr int SM_B2 = SM_B1 + 224;
constexpr int SM_EP = SM_B2 + 16;
constexpr int SM_QS = SM_EP + 16;
constexpr int SM_OS = SM_QS + 2304;
constexpr int SM_HS = SM_OS + 1152;
constexpr int SM_RED = SM_HS + 960;
constexpr int SM_MX = SM_RED + 2048;
constexpr int SM_LS = SM_MX + 256;
constexpr int SM_BAR = SM_LS + 256;
constexpr int SM_FLAG = SM_BAR + (2 * NSTAGE + 2) * 8;
constexpr int SM_TOTAL = SM_FLAG + 8;
constexpr int SM_ALLOC = SM_TOTAL + 1024;

constexpr int XS_STRIDE = 1032 * 2;
constexpr int YS_STRIDE = 520 * 2;
constexpr int HS_STRIDE = 240;
constexpr int FR_STRIDE = 288;

#define PACE_T 668
#define PACE_LEAD 2
#define PW_J 6
#define PACE_CAP 6

constexpr int BAR_INIT = 0;
constexpr int BAR_CONS = 1;
constexpr int BAR_PAIR = 2;
constexpr int BAR_X = 6;
constexpr int BAR_Q = 7;
constexpr int BAR_O = 8;
constexpr int BAR_OS = 9;
constexpr int BAR_W1 = 10;
constexpr int BAR_HS = 11;
constexpr int BAR_A = 12;
constexpr int BAR_B = 13;

struct TMaps {
    CUtensorMap wq, w1, k, v, w2, wo;
};

__device__ __align__(256) unsigned int g_epoch[NCTA * 4];
__device__ __align__(256) unsigned int g_q[2 * 4 * 4096];
__device__ __align__(256) unsigned int g_h[2 * F_DIM * 4];
__device__ __align__(256) unsigned int g_o1[NCTA * 8 * 128];
__device__ __align__(256) unsigned int g_ml[NCTA * 8 * 8];
__device__ __align__(256) unsigned int g_o2[32 * 4 * 128];
__device__ __align__(256) unsigned int g_a[NCTA * 32 * 32];
__device__ __align__(256) unsigned int g_b[NCTA * 32 * 32];

#define PROF(i)
#define PROFW(w, i)
__device__ __forceinline__ uint32_t smem_u32(const void* p) { return (uint32_t)__cvta_generic_to_shared(p); }
__device__ __forceinline__ uint32_t gtime32() { uint32_t t; asm volatile("mov.u32 %0, %globaltimer_lo;" : "=r"(t)); return t; }

__device__ __forceinline__ void mbar_init(uint32_t bar, uint32_t cnt) {
    asm volatile("mbarrier.init.shared::cta.b64 [%0], %1;" ::"r"(bar), "r"(cnt) : "memory");
}
__device__ __forceinline__ void mbar_expect_tx(uint32_t bar, uint32_t bytes) {
    asm volatile("mbarrier.arrive.expect_tx.shared::cta.b64 _, [%0], %1;" ::"r"(bar), "r"(bytes) : "memory");
}
__device__ __forceinline__ void mbar_arrive_cnt(uint32_t bar, uint32_t cnt) {
    asm volatile("mbarrier.arrive.shared::cta.b64 _, [%0], %1;" ::"r"(bar), "r"(cnt) : "memory");
}
__device__ __forceinline__ bool mbar_try(uint32_t bar, uint32_t parity) {
    uint32_t ok;
    asm volatile(
        "{\n.reg .pred p;\n"
        "mbarrier.try_wait.parity.shared::cta.b64 p, [%1], %2;\n"
        "selp.u32 %0, 1, 0, p;\n}\n"
        : "=r"(ok)
        : "r"(bar), "r"(parity)
        : "memory");
    return ok != 0;
}
__device__ __noinline__ void mbar_wait_slow(uint32_t bar, uint32_t parity, volatile uint32_t* flag) {
    long long t0 = clock64();
    for (uint32_t it = 0; it < 0x40000000u; it++) {
        if (mbar_try(bar, parity)) return;
        if ((it & 63u) == 63u) {
            if (*flag) return;
            if (clock64() - t0 > 2000000000LL) { *flag = 1u; return; }
        }
    }
}
__device__ __forceinline__ void mbar_wait(uint32_t bar, uint32_t parity, volatile uint32_t* flag) {
    if (mbar_try(bar, parity)) return;
    if (mbar_try(bar, parity)) return;
    mbar_wait_slow(bar, parity, flag);
}

__device__ __forceinline__ void tma_2d(uint32_t dst, const CUtensorMap* tm, int c0, int c1, uint32_t bar) {
    asm volatile(
        "cp.async.bulk.tensor.2d.shared::cluster.global.mbarrier::complete_tx::bytes.L2::cache_hint [%0], [%1, {%3, %4}], [%2], %5;"
        ::"r"(dst), "l"(tm), "r"(bar), "r"(c0), "r"(c1), "l"(0x12F0000000000000ull)
        : "memory");
}
__device__ __forceinline__ void tma_3d(uint32_t dst, const CUtensorMap* tm, int c0, int c1, int c2, uint32_t bar) {
    asm volatile(
        "cp.async.bulk.tensor.3d.shared::cluster.global.mbarrier::complete_tx::bytes.L2::cache_hint [%0], [%1, {%3, %4, %5}], [%2], %6;"
        ::"r"(dst), "l"(tm), "r"(bar), "r"(c0), "r"(c1), "r"(c2), "l"(0x12F0000000000000ull)
        : "memory");
}
__device__ __forceinline__ void bulk_load(uint32_t dst, const void* src, uint32_t bytes, uint32_t bar) {
    asm volatile("cp.async.bulk.shared::cluster.global.mbarrier::complete_tx::bytes [%0], [%1], %2, [%3];"
                 ::"r"(dst), "l"(src), "r"(bytes), "r"(bar)
                 : "memory");
}
__device__ __forceinline__ void prefetch_tmap(const CUtensorMap* tm) {
    asm volatile("prefetch.tensormap [%0];" ::"l"(tm) : "memory");
}
__device__ __forceinline__ void bar_sync(int id, int cnt) { asm volatile("bar.sync %0, %1;" ::"r"(id), "r"(cnt) : "memory"); }
__device__ __forceinline__ void bar_arrive(int id, int cnt) { asm volatile("bar.arrive %0, %1;" ::"r"(id), "r"(cnt) : "memory"); }

__device__ __forceinline__ void ldsm_x4(uint32_t (&r)[4], uint32_t addr) {
    asm volatile("ldmatrix.sync.aligned.m8n8.x4.shared.b16 {%0,%1,%2,%3}, [%4];"
                 : "=r"(r[0]), "=r"(r[1]), "=r"(r[2]), "=r"(r[3])
                 : "r"(addr)
                 : "memory");
}
__device__ __forceinline__ void ldsm_x4_t(uint32_t (&r)[4], uint32_t addr) {
    asm volatile("ldmatrix.sync.aligned.m8n8.x4.trans.shared.b16 {%0,%1,%2,%3}, [%4];"
                 : "=r"(r[0]), "=r"(r[1]), "=r"(r[2]), "=r"(r[3])
                 : "r"(addr)
                 : "memory");
}
__device__ __forceinline__ void mma16816(float (&c)[4], const uint32_t (&a)[4], uint32_t b0, uint32_t b1) {
    asm volatile(
        "mma.sync.aligned.m16n8k16.row.col.f32.bf16.bf16.f32 {%0,%1,%2,%3}, {%4,%5,%6,%7}, {%8,%9}, {%0,%1,%2,%3};"
        : "+f"(c[0]), "+f"(c[1]), "+f"(c[2]), "+f"(c[3])
        : "r"(a[0]), "r"(a[1]), "r"(a[2]), "r"(a[3]), "r"(b0), "r"(b1));
}
__device__ __forceinline__ uint32_t lds32(uint32_t addr) {
    uint32_t v;
    asm volatile("ld.shared.b32 %0, [%1];" : "=r"(v) : "r"(addr) : "memory");
    return v;
}
__device__ __forceinline__ uint2 lds64(uint32_t addr) {
    uint2 v;
    asm volatile("ld.shared.v2.b32 {%0, %1}, [%2];" : "=r"(v.x), "=r"(v.y) : "r"(addr) : "memory");
    return v;
}
__device__ __forceinline__ void sts32(uint32_t addr, uint32_t v) {
    asm volatile("st.shared.b32 [%0], %1;" ::"r"(addr), "r"(v) : "memory");
}
__device__ __forceinline__ void sts64(uint32_t addr, uint32_t a, uint32_t b) {
    asm volatile("st.shared.v2.b32 [%0], {%1, %2};" ::"r"(addr), "r"(a), "r"(b) : "memory");
}

__device__ __forceinline__ float bf16r(float x) { return __bfloat162float(__float2bfloat16_rn(x)); }
__device__ __forceinline__ uint32_t pack_bf16(float lo, float hi) {
    __nv_bfloat162 v = __floats2bfloat162_rn(lo, hi);
    return *reinterpret_cast<uint32_t*>(&v);
}
__device__ __forceinline__ float bf_lo(uint32_t u) { return __uint_as_float(u << 16); }
__device__ __forceinline__ float bf_hi(uint32_t u) { return __uint_as_float(u & 0xffff0000u); }

__device__ __forceinline__ uint32_t enc(float v, uint32_t tag) { return (__float_as_uint(v) & ~3u) | tag; }
__device__ __forceinline__ float dec(uint32_t u) { return __uint_as_float(u & ~3u); }
__device__ __forceinline__ void st2(unsigned int* p, uint32_t a, uint32_t b) {
    asm volatile("st.relaxed.gpu.global.v2.b32 [%0], {%1, %2};" ::"l"(p), "r"(a), "r"(b) : "memory");
}
__device__ __forceinline__ void st4(unsigned int* p, uint32_t a, uint32_t b, uint32_t c, uint32_t d) {
    asm volatile("st.relaxed.gpu.global.v4.b32 [%0], {%1, %2, %3, %4};" ::"l"(p), "r"(a), "r"(b), "r"(c), "r"(d) : "memory");
}
__device__ __forceinline__ uint32_t ld1(const unsigned int* p) {
    uint32_t v;
    asm volatile("ld.relaxed.gpu.global.b32 %0, [%1];" : "=r"(v) : "l"(p) : "memory");
    return v;
}
__device__ __forceinline__ uint2 ld2(const unsigned int* p) {
    uint2 v;
    asm volatile("ld.relaxed.gpu.global.v2.b32 {%0, %1}, [%2];" : "=r"(v.x), "=r"(v.y) : "l"(p) : "memory");
    return v;
}
__device__ __forceinline__ uint4 ld4(const unsigned int* p) {
    uint4 v;
    asm volatile("ld.relaxed.gpu.global.v4.b32 {%0, %1, %2, %3}, [%4];" : "=r"(v.x), "=r"(v.y), "=r"(v.z), "=r"(v.w) : "l"(p) : "memory");
    return v;
}
__device__ __forceinline__ uint32_t bad4(const uint4& v, uint32_t tag) { return (v.x ^ tag) | (v.y ^ tag) | (v.z ^ tag) | (v.w ^ tag); }
__device__ __forceinline__ bool warp_ok(uint32_t bad) { return __all_sync(0xffffffffu, (bad & 3u) == 0u); }
constexpr uint32_t POLL_LIMIT = 1u << 21;

__device__ __forceinline__ void gemv_tile4(float (&acc0)[4], float (&acc1)[4], uint32_t a_addr, uint32_t b_addr, bool bvalid) {
    uint32_t a[4][4];
    uint32_t b[4][2];
#pragma unroll
    for (int ks = 0; ks < 4; ks++) ldsm_x4_t(a[ks], a_addr + ks * 2048);
#pragma unroll
    for (int ks = 0; ks < 4; ks++) {
        b[ks][0] = bvalid ? lds32(b_addr + ks * 32) : 0u;
        b[ks][1] = bvalid ? lds32(b_addr + ks * 32 + 16) : 0u;
    }
#pragma unroll
    for (int ks = 0; ks < 4; ks++) {
        if (ks & 1) mma16816(acc1, a[ks], b[ks][0], b[ks][1]);
        else mma16816(acc0, a[ks], b[ks][0], b[ks][1]);
    }
}

__device__ __forceinline__ float final_sum(const unsigned int* buf, int lane, uint32_t tag, bool backoff) {
    const unsigned int* p = buf + (lane >> 3) * 256 + (lane & 7) * 4;
    uint4 d[8];
    for (uint32_t it = 0; it < POLL_LIMIT; it++) {
        uint32_t bad = 0;
#pragma unroll
        for (int i = 0; i < 8; i++) { d[i] = ld4(p + i * 32); bad |= bad4(d[i], tag); }
        if (warp_ok(bad)) break;
        if (backoff) __nanosleep(100);
    }
    float s0 = 0.f, s1 = 0.f, s2 = 0.f, s3 = 0.f;
#pragma unroll
    for (int i = 0; i < 8; i++) { s0 += dec(d[i].x); s1 += dec(d[i].y); s2 += dec(d[i].z); s3 += dec(d[i].w); }
    const bool hi = lane & 16;
    float u0 = hi ? s0 : s2, u1 = hi ? s1 : s3;
    float k0 = hi ? s2 : s0, k1 = hi ? s3 : s1;
    k0 += __shfl_xor_sync(0xffffffffu, u0, 16);
    k1 += __shfl_xor_sync(0xffffffffu, u1, 16);
    const bool od = lane & 8;
    const float w = od ? k0 : k1;
    float r = od ? k1 : k0;
    r += __shfl_xor_sync(0xffffffffu, w, 8);
    return r;
}

__global__ void __launch_bounds__(NTHREADS, 1)
fused_kernel(const __grid_constant__ TMaps maps,
             const __nv_bfloat16* __restrict__ x, const __nv_bfloat16* __restrict__ b1,
             const __nv_bfloat16* __restrict__ b2, const __nv_bfloat16* __restrict__ gate_w,
             __nv_bfloat16* __restrict__ out) {
    extern __shared__ unsigned char smem_raw[];
    const uint32_t sbase = (smem_u32(smem_raw) + 1023u) & ~1023u;
    unsigned char* sptr = smem_raw + (sbase - smem_u32(smem_raw));
    volatile uint32_t* flag = reinterpret_cast<volatile uint32_t*>(sptr + SM_FLAG);

    const int c = blockIdx.x;
    const int tid = threadIdx.x;
    const int warp = tid >> 5;
    const int lane = tid & 31;
    const bool has_w1 = c < 112;
    const int kb = c >> 2, nb = c & 3;
    const uint32_t bar_full = sbase + SM_BAR;
    const uint32_t bar_empty = sbase + SM_BAR + NSTAGE * 8;
    const uint32_t bar_x = sbase + SM_BAR + 2 * NSTAGE * 8;
    const uint32_t bar_g = bar_x + 8;

    PROFW(0, 0);
    if (warp == 8) {
        const int n_w1 = has_w1 ? 4 : 0;
        const int n_tiles = 44 + n_w1;
        const int kv_row0 = (c >> 3) * SK + (c & 7) * 1024;
        uint32_t due = 0;
        if (lane == 0) {
#pragma unroll
            for (int j = 0; j < PACE_LEAD; j++) mbar_init(bar_full + j * 8, 1);
            mbar_init(bar_x, 1);
            asm volatile("fence.mbarrier_init.release.cluster;" ::: "memory");
            asm volatile("fence.proxy.async.shared::cta;" ::: "memory");
#pragma unroll
            for (int j = 0; j < PACE_LEAD; j++) {
                mbar_expect_tx(bar_full + j * 8, STAGE_BYTES);
                tma_2d(sbase + j * STAGE_BYTES, &maps.wq, (c >> 1) * 64, (c & 1) * 512 + j * 128, bar_full + j * 8);
            }
            due = gtime32() + PACE_T + (c >> 1) * PACE_T / 64;
            mbar_expect_tx(bar_x, 4 * 2048 + 16);
#pragma unroll
            for (int b = 0; b < 4; b++) bulk_load(sbase + SM_XS + b * XS_STRIDE, x + b * D_MODEL, 2048, bar_x);
            bulk_load(sbase + SM_EP, g_epoch + c * 4, 16, bar_x);
#pragma unroll
            for (int i = PACE_LEAD; i < NSTAGE; i++) mbar_init(bar_full + i * 8, 1);
#pragma unroll
            for (int i = 0; i < NSTAGE; i++) mbar_init(bar_empty + i * 8, 8);
            mbar_init(bar_g, 1);
            *flag = 0u;
            asm volatile("fence.mbarrier_init.release.cluster;" ::: "memory");
            asm volatile("fence.proxy.async.shared::cta;" ::: "memory");
            mbar_expect_tx(bar_g, 2048 + 224 + 16);
            bulk_load(sbase + SM_GW, gate_w, 2048, bar_g);
            bulk_load(sbase + SM_B1, b1 + kb * 112, 224, bar_g);
            bulk_load(sbase + SM_B2, b2 + c * 8, 16, bar_g);
            prefetch_tmap(&maps.k);
            prefetch_tmap(&maps.v);
            prefetch_tmap(&maps.w1);
            prefetch_tmap(&maps.wo);
            prefetch_tmap(&maps.w2);
        }
        __syncwarp();
        bar_arrive(BAR_INIT, NTHREADS);
        if (lane == 0) {
            int landed = 0;
            for (int i = PACE_LEAD; i < n_tiles; i++) {
                while (landed + PACE_CAP <= i) {
                    mbar_wait(bar_full + (landed % NSTAGE) * 8, (uint32_t)(landed / NSTAGE) & 1u, flag);
                    landed++;
                }
                const int stage = i % NSTAGE;
                if (i >= NSTAGE) mbar_wait(bar_empty + stage * 8, (uint32_t)(i / NSTAGE - 1) & 1u, flag);
                for (int it = 0; it < 100000 && (int)(gtime32() - due) < 0; it++) {}
                due += (i >= 36 && i < 36 + n_w1) ? PACE_T * 7 / 8 : PACE_T;
                if (i == 35 && !has_w1) due += PACE_T * 7 / 2;
                const uint32_t dst = sbase + stage * STAGE_BYTES;
                const uint32_t fb = bar_full + stage * 8;
                int j = i - 4;
                if (j < 0) {
                    mbar_expect_tx(fb, STAGE_BYTES);
                    tma_2d(dst, &maps.wq, (c >> 1) * 64, (c & 1) * 512 + i * 128, fb);
                } else if (j < 32) {
                    mbar_expect_tx(fb, STAGE_BYTES);
                    tma_3d(dst, j < 16 ? &maps.k : &maps.v, 0, kv_row0 + (j & 15) * 64, 0, fb);
                } else if (j < 32 + n_w1) {
                    mbar_expect_tx(fb, STAGE_BYTES);
                    tma_2d(dst, &maps.w1, (c >> 1) * 64, (c & 1) * 512 + (j - 32) * 128, fb);
                } else {
                    j -= 32 + n_w1;
                    const CUtensorMap* tm = j < 4 ? &maps.wo : &maps.w2;
                    const int row = j < 4 ? kb * 128 + j * 32 : kb * 112 + (j - 4) * 32;
                    mbar_expect_tx(fb, j < 7 ? STAGE_BYTES : STAGE_BYTES / 2);
                    tma_3d(dst, tm, 0, row, nb * 4, fb);
                    if (j < 7) tma_3d(dst + 8192, tm, 0, row + 16, nb * 4, fb);
                }
            }
            PROF(20);
        }
        return;
    }

    bar_sync(BAR_INIT, NTHREADS);
    if (warp < 4 && (lane & 3) < 2) {
        unsigned int* p = g_q + ((c & 1) * 4 + 2 * (lane & 3)) * 4096 + (c >> 1) * 64 + warp * 16 + 2 * (lane >> 2);
        st2(p, 0u, 0u);
        st2(p + 4096, 0u, 0u);
    }
    mbar_wait(bar_x, 0, flag);
    const uint32_t epoch = *reinterpret_cast<volatile unsigned int*>(sptr + SM_EP) + 1u;
    const uint32_t tag = 1u + epoch % 3u;
    const int g = lane >> 2;
    const int t = lane & 3;
    const int khalf = c & 1;
    const int pair = c >> 3;

    if (warp == 9) {
        float gate;
        mbar_wait(bar_g, 0, flag);
        {
            float z[4];
            uint4 gw[4];
#pragma unroll
            for (int i = 0; i < 4; i++) gw[i] = *reinterpret_cast<const uint4*>(sptr + SM_GW + (i * 32 + lane) * 16);
#pragma unroll 1
            for (int b = 0; b < 4; b++) {
                uint4 xv[4];
#pragma unroll
                for (int i = 0; i < 4; i++) xv[i] = *reinterpret_cast<const uint4*>(sptr + SM_XS + b * XS_STRIDE + (i * 32 + lane) * 16);
                float s = 0.f, zs = 0.f;
#pragma unroll
                for (int i = 0; i < 4; i++) {
                    const uint32_t xa[4] = {xv[i].x, xv[i].y, xv[i].z, xv[i].w};
                    const uint32_t wa[4] = {gw[i].x, gw[i].y, gw[i].z, gw[i].w};
#pragma unroll
                    for (int e = 0; e < 4; e++) {
                        s += bf_lo(xa[e]) + bf_hi(xa[e]);
                        zs += bf16r(bf_lo(xa[e]) * bf_lo(wa[e]));
                        zs += bf16r(bf_hi(xa[e]) * bf_hi(wa[e]));
                    }
                }
#pragma unroll
                for (int o = 16; o > 0; o >>= 1) {
                    s += __shfl_xor_sync(0xffffffffu, s, o);
                    zs += __shfl_xor_sync(0xffffffffu, zs, o);
                }
                if (b == 0) z[0] = zs;
                if (b == 1) z[1] = zs;
                if (b == 2) z[2] = zs;
                if (b == 3) z[3] = zs;
                const float mean = s * (1.0f / 1024.0f);
                float q = 0.f;
#pragma unroll
                for (int i = 0; i < 4; i++) {
                    const uint32_t xa[4] = {xv[i].x, xv[i].y, xv[i].z, xv[i].w};
#pragma unroll
                    for (int e = 0; e < 4; e++) {
                        const float d0 = bf_lo(xa[e]) - mean, d1 = bf_hi(xa[e]) - mean;
                        q += d0 * d0 + d1 * d1;
                    }
                }
#pragma unroll
                for (int o = 16; o > 0; o >>= 1) q += __shfl_xor_sync(0xffffffffu, q, o);
                const float mb = bf16r(mean);
                const float vb = bf16r(q * (1.0f / 1024.0f));
                const float den = bf16r(sqrtf(bf16r(vb + 1e-5f)));
#pragma unroll
                for (int i = 0; i < 2; i++) {
                    const uint4 xs = khalf ? xv[2 + i] : xv[i];
                    const uint32_t xa[4] = {xs.x, xs.y, xs.z, xs.w};
                    uint32_t ya[4];
#pragma unroll
                    for (int e = 0; e < 4; e++) {
                        const float y0 = bf16r(bf_lo(xa[e]) - mb) / den;
                        const float y1 = bf16r(bf_hi(xa[e]) - mb) / den;
                        ya[e] = pack_bf16(y0, y1);
                    }
                    *reinterpret_cast<uint4*>(sptr + SM_YS + b * YS_STRIDE + (i * 256 + lane * 8) * 2) = make_uint4(ya[0], ya[1], ya[2], ya[3]);
                }
            }
            const int sg = lane >> 3;
            float zz = sg == 0 ? z[0] : (sg == 1 ? z[1] : (sg == 2 ? z[2] : z[3]));
            zz = bf16r(zz);
            gate = bf16r(1.0f / (1.0f + __expf(-zz)));
        }
        const float b2v = __bfloat162float(*reinterpret_cast<const __nv_bfloat16*>(sptr + SM_B2 + (lane & 7) * 2));
        bar_arrive(BAR_X, 288);
        PROF(12);

        bar_sync(BAR_O, 320);
        {
            uint2 mlv;
            uint4 d[8];
            const unsigned int* pm = g_ml + c * 64 + (lane & 7) * 8;
            const unsigned int* po = g_o1 + (size_t)c * 1024 + lane * 4;
            for (uint32_t it = 0; it < POLL_LIMIT; it++) {
                mlv = ld2(pm);
                uint32_t bad = (mlv.x ^ tag) | (mlv.y ^ tag);
#pragma unroll
                for (int s = 0; s < 8; s++) { d[s] = ld4(po + s * 128); bad |= bad4(d[s], tag); }
                if (warp_ok(bad)) break;
                __nanosleep(40);
            }
            float f;
            {
                const float m = dec(mlv.x), l = dec(mlv.y);
                float M = m;
#pragma unroll
                for (int o = 4; o > 0; o >>= 1) M = fmaxf(M, __shfl_xor_sync(0xffffffffu, M, o));
                const float w = exp2f((m - M) * 1.4426950408889634f);
                float L = w * l;
#pragma unroll
                for (int o = 4; o > 0; o >>= 1) L += __shfl_xor_sync(0xffffffffu, L, o);
                f = w / L;
            }
            float o0 = 0.f, o1 = 0.f, o2 = 0.f, o3 = 0.f;
#pragma unroll
            for (int s = 0; s < 8; s++) {
                const float fs = __shfl_sync(0xffffffffu, f, s);
                o0 = fmaf(fs, dec(d[s].x), o0);
                o1 = fmaf(fs, dec(d[s].y), o1);
                o2 = fmaf(fs, dec(d[s].z), o2);
                o3 = fmaf(fs, dec(d[s].w), o3);
            }
            const int b = pair >> 2, head = (pair & 3) * 8 + (c & 7);
            st4(g_o2 + (head * 4 + b) * 128 + lane * 4, enc(bf16r(o0), tag), enc(bf16r(o2), tag), enc(bf16r(o1), tag), enc(bf16r(o3), tag));
        }
        PROF(15);
        bar_sync(BAR_A, 288);
        const float aterm = bf16r(gate * bf16r(final_sum(g_a + (size_t)c * 1024, lane, tag, true)));
        PROF(17);
        bar_sync(BAR_B, 288);
        {
            const float bv = bf16r(bf16r(final_sum(g_b + (size_t)c * 1024, lane, tag, false)) + b2v);
            const float bterm = bf16r(bf16r(1.0f - gate) * bv);
            out[(lane >> 3) * D_MODEL + c * 8 + (lane & 7)] = __float2bfloat16_rn(aterm + bterm);
        }
        PROF(19);
        if (lane == 0) *reinterpret_cast<volatile unsigned int*>(&g_epoch[c * 4]) = epoch;
        return;
    }
    if (warp == 10) {
        mbar_wait(bar_full + 3 * 8, 0, flag);
        {
            const unsigned int* p = g_q + ((lane >> 4) * 4 + (pair >> 2)) * 4096 + (pair & 3) * 1024 + (lane & 15) * 64 + 15;
            for (uint32_t it = 0; it < POLL_LIMIT; it++) {
                __nanosleep(150);
                const uint32_t bad = (ld1(p) ^ tag) | (ld1(p + 16) ^ tag) | (ld1(p + 32) ^ tag) | (ld1(p + 48) ^ tag);
                if (warp_ok(bad)) break;
            }
        }
        bar_arrive(BAR_Q, 288);
        PROF(13);
        bar_sync(BAR_O, 320);
        {
            const unsigned int* p = g_o2 + kb * 512 + lane * 4;
            uint4 d[4];
            __nanosleep(400);
            for (uint32_t it = 0; it < POLL_LIMIT; it++) {
                uint32_t bad = 0;
#pragma unroll
                for (int b = 0; b < 4; b++) { d[b] = ld4(p + b * 128); bad |= bad4(d[b], tag); }
                if (warp_ok(bad)) break;
                __nanosleep(100);
            }
#pragma unroll
            for (int b = 0; b < 4; b++)
                sts64(sbase + SM_OS + b * FR_STRIDE + lane * 8, __byte_perm(d[b].x, d[b].y, 0x7632), __byte_perm(d[b].z, d[b].w, 0x7632));
        }
        bar_arrive(BAR_OS, 288);
        PROF(14);
        return;
    }
    if (warp == 11) {
        mbar_wait(bar_g, 0, flag);
        bar_sync(BAR_W1, 288);
        {
            const unsigned int* p = g_h + (kb * 112 + lane) * 4;
            const bool has4 = lane < 16;
            uint4 d[4][2];
            for (uint32_t it = 0; it < POLL_LIMIT; it++) {
                uint32_t bad = 0;
#pragma unroll
                for (int i = 0; i < 4; i++) {
                    if (i < 3 || has4) {
                        d[i][0] = ld4(p + i * 128);
                        d[i][1] = ld4(p + i * 128 + F_DIM * 4);
                        bad |= bad4(d[i][0], tag) | bad4(d[i][1], tag);
                    }
                }
                if (warp_ok(bad)) break;
                __nanosleep(100);
            }
            PROF(16);
#pragma unroll
            for (int i = 0; i < 4; i++) {
                if (i < 3 || has4) {
                    const int cl = i * 32 + lane;
                    const float bias = __bfloat162float(*reinterpret_cast<const __nv_bfloat16*>(sptr + SM_B1 + cl * 2));
                    const uint32_t u0[4] = {d[i][0].x, d[i][0].y, d[i][0].z, d[i][0].w};
                    const uint32_t u1[4] = {d[i][1].x, d[i][1].y, d[i][1].z, d[i][1].w};
#pragma unroll
                    for (int b = 0; b < 4; b++) {
                        float v = bf16r(dec(u0[b]) + dec(u1[b]));
                        v = bf16r(v + bias);
                        const float inner = 0.7978845608028654f * (v + 0.044715f * v * v * v);
                        const float hv = 0.5f * v * (1.0f + tanhf(inner));
                        *reinterpret_cast<__nv_bfloat16*>(sptr + SM_HS + b * HS_STRIDE + cl * 2) = __float2bfloat16_rn(hv);
                    }
                }
            }
        }
        bar_arrive(BAR_HS, 288);
        PROF(18);
        return;
    }

    const int mt = warp & 3;
    const int kh2 = warp >> 2;
    PROFW(0, 1);

    int stage = 0;
    uint32_t ph = 0;
    const uint32_t l8 = lane & 7;
    const uint32_t rowT = (l8 + 8 * (lane >> 4)) * 128;
    const uint32_t offT = rowT + ((((uint32_t)(2 * mt + ((lane >> 3) & 1))) ^ l8) << 4);
    const bool bvalid = g < 4;
    const size_t dst_off = ((size_t)(nb * 32 + warp * 4) * 32 + kb) * 32 + g * 4 + 2 * t;

    {
        float acc0[4] = {0.f, 0.f, 0.f, 0.f}, acc1[4] = {0.f, 0.f, 0.f, 0.f};
        const uint32_t baddr = sbase + SM_XS + (g & 3) * XS_STRIDE + (khalf * 512 + kh2 * 64 + 2 * t) * 2;
#pragma unroll 1
        for (int j = 0; j < 4; j++) {
            mbar_wait(bar_full + stage * 8, ph, flag);
            gemv_tile4(acc0, acc1, sbase + stage * STAGE_BYTES + kh2 * 8192 + offT, baddr + j * 256, bvalid);
            __syncwarp();
            if (lane == 0) mbar_arrive_cnt(bar_empty + stage * 8, 1);
            ++stage;
        }
        float4* red = reinterpret_cast<float4*>(sptr + SM_RED) + mt * 16 + (g * 2 + (t & 1));
        if (kh2 == 1 && t < 2) *red = make_float4(acc0[0] + acc1[0], acc0[1] + acc1[1], acc0[2] + acc1[2], acc0[3] + acc1[3]);
        bar_sync(BAR_PAIR + mt, 64);
        if (kh2 == 0 && t < 2) {
            const float4 o = *red;
            unsigned int* p = g_q + (khalf * 4 + 2 * t) * 4096 + (c >> 1) * 64 + mt * 16 + 2 * g;
            st2(p, enc(acc0[0] + acc1[0] + o.x, tag), enc(acc0[2] + acc1[2] + o.z, tag));
            st2(p + 4096, enc(acc0[1] + acc1[1] + o.y, tag), enc(acc0[3] + acc1[3] + o.w, tag));
        }
    }
    PROFW(0, 2);
    uint32_t qf[8][2];
    {
        bar_sync(BAR_Q, 288);
        const unsigned int* p = g_q + (pair >> 2) * 4096 + (pair & 3) * 1024 + tid * 4;
        uint4 d0, d1;
        for (uint32_t it = 0; it < POLL_LIMIT; it++) {
            d0 = ld4(p);
            d1 = ld4(p + 4 * 4096);
            if (warp_ok(bad4(d0, tag) | bad4(d1, tag))) break;
            __nanosleep(100);
        }
        sts64(sbase + SM_QS + warp * FR_STRIDE + lane * 8,
              pack_bf16(dec(d0.x) + dec(d1.x), dec(d0.z) + dec(d1.z)), pack_bf16(dec(d0.y) + dec(d1.y), dec(d0.w) + dec(d1.w)));
        bar_sync(BAR_CONS, 256);
#pragma unroll
        for (int ks = 0; ks < 8; ks++) {
            const uint2 v = lds64(sbase + SM_QS + g * FR_STRIDE + (ks * 4 + t) * 8);
            qf[ks][0] = v.x;
            qf[ks][1] = v.y;
        }
    }
    PROFW(0, 4);
    float sc[8][4];
    {
        int st = stage + kh2;
        uint32_t php = ph;
        const uint32_t krow = mt * 16 + l8 + 8 * ((lane >> 3) & 1);
        const uint32_t khi = lane >> 4;
#pragma unroll
        for (int i = 0; i < 8; i++) {
            mbar_wait(bar_full + st * 8, php, flag);
            const uint32_t base = sbase + st * STAGE_BYTES + krow * 128;
            float c0[4] = {0.f, 0.f, 0.f, 0.f}, c1[4] = {0.f, 0.f, 0.f, 0.f};
            uint32_t a[8][4];
#pragma unroll
            for (int ks = 0; ks < 8; ks++)
                ldsm_x4(a[ks], base + (ks >> 2) * 8192 + (((uint32_t)((ks & 3) * 2) + khi) ^ l8) * 16);
#pragma unroll
            for (int ks = 0; ks < 8; ks++) {
                if (ks & 1) mma16816(c1, a[ks], qf[ks][0], qf[ks][1]);
                else mma16816(c0, a[ks], qf[ks][0], qf[ks][1]);
            }
            __syncwarp();
            if (lane == 0) mbar_arrive_cnt(bar_empty + st * 8, 2);
#pragma unroll
            for (int e = 0; e < 4; e++) sc[i][e] = bf16r(bf16r(c0[e] + c1[e]) * 0.08838834764831845f);
            st += 2;
            if (st >= NSTAGE) { st -= NSTAGE; php ^= 1u; }
        }
        stage += 16 - NSTAGE;
        ph ^= 1u;
    }
    PROFW(0, 5);
    float ml[4] = {0.f, 0.f, 0.f, 0.f};
    {
        float m0 = sc[0][0], m1 = sc[0][1];
#pragma unroll
        for (int i = 0; i < 8; i++) {
            m0 = fmaxf(m0, fmaxf(sc[i][0], sc[i][2]));
            m1 = fmaxf(m1, fmaxf(sc[i][1], sc[i][3]));
        }
#pragma unroll
        for (int o = 4; o < 32; o <<= 1) {
            m0 = fmaxf(m0, __shfl_xor_sync(0xffffffffu, m0, o));
            m1 = fmaxf(m1, __shfl_xor_sync(0xffffffffu, m1, o));
        }
        float2* mx = reinterpret_cast<float2*>(sptr + SM_MX);
        if (g == 0) mx[warp * 4 + t] = make_float2(m0, m1);
        bar_sync(BAR_X, 288);
#pragma unroll
        for (int w = 0; w < 8; w++) {
            const float2 v = mx[w * 4 + t];
            m0 = fmaxf(m0, v.x);
            m1 = fmaxf(m1, v.y);
        }
        float l0 = 0.f, l1 = 0.f;
#pragma unroll
        for (int i = 0; i < 8; i++) {
            const float e0 = exp2f((sc[i][0] - m0) * 1.4426950408889634f);
            const float e1 = exp2f((sc[i][1] - m1) * 1.4426950408889634f);
            const float e2 = exp2f((sc[i][2] - m0) * 1.4426950408889634f);
            const float e3 = exp2f((sc[i][3] - m1) * 1.4426950408889634f);
            l0 += e0 + e2;
            l1 += e1 + e3;
            const uint32_t key = (2 * i + kh2) * 64 + mt * 16 + g;
            sts32(sbase + SM_P + key * 16 + t * 4, pack_bf16(e0, e1));
            sts32(sbase + SM_P + (key + 8) * 16 + t * 4, pack_bf16(e2, e3));
        }
#pragma unroll
        for (int o = 4; o < 32; o <<= 1) {
            l0 += __shfl_xor_sync(0xffffffffu, l0, o);
            l1 += __shfl_xor_sync(0xffffffffu, l1, o);
        }
        float2* ls = reinterpret_cast<float2*>(sptr + SM_LS);
        if (g == 0) ls[warp * 4 + t] = make_float2(l0, l1);
        bar_sync(BAR_CONS, 256);
        if (warp == 0) {
#pragma unroll
            for (int w = 0; w < 8; w++) {
                const float2 v = ls[w * 4 + t];
                ml[1] += v.x;
                ml[3] += v.y;
            }
            ml[0] = m0;
            ml[2] = m1;
            unsigned int* pm = g_ml + ((pair * 8 + 2 * t + (g >> 2)) * 8 + (c & 7)) * 8 + (g & 3) * 2;
            st2(pm, enc(g < 4 ? ml[0] : ml[2], tag), enc(g < 4 ? ml[1] : ml[3], tag));
        }
    }
    PROFW(0, 6);
    {
        float acc0[4] = {0.f, 0.f, 0.f, 0.f}, acc1[4] = {0.f, 0.f, 0.f, 0.f};
        const uint32_t paddr = sbase + SM_P + lane * 16;
        unsigned int* p = g_o1 + ((size_t)(pair * 8 + 2 * t) * 8 + (c & 7)) * 128 + warp * 16 + 2 * g;
#pragma unroll 1
        for (int j = 0; j < 16; j++) {
            if (j == PW_J) {
                st2(p, 0u, 0u);
                st2(p + 1024, 0u, 0u);
                if (t < 2) {
#pragma unroll
                    for (int e = 0; e < 4; e++) {
                        st2(g_a + dst_off + e * 1024, 0u, 0u);
                        st2(g_b + dst_off + e * 1024, 0u, 0u);
                    }
                    if (kh2 == 0 && has_w1) {
                        unsigned int* ph_ = g_h + (khalf * F_DIM + (c >> 1) * 64 + mt * 16 + g) * 4 + 2 * t;
                        st2(ph_, 0u, 0u);
                        st2(ph_ + 32, 0u, 0u);
                    }
                }
                if (warp == 7) st4(g_o2 + (((pair & 3) * 8 + (c & 7)) * 4 + (pair >> 2)) * 128 + lane * 4, 0u, 0u, 0u, 0u);
            }
            uint32_t pb[2][4];
            ldsm_x4_t(pb[0], paddr + j * 1024);
            ldsm_x4_t(pb[1], paddr + j * 1024 + 512);
            mbar_wait(bar_full + stage * 8, ph, flag);
            const uint32_t base = sbase + stage * STAGE_BYTES + kh2 * 8192 + offT;
            uint32_t a[4][4];
#pragma unroll
            for (int ks = 0; ks < 4; ks++) ldsm_x4_t(a[ks], base + ks * 2048);
            mma16816(acc0, a[0], pb[0][0], pb[0][1]);
            mma16816(acc1, a[1], pb[0][2], pb[0][3]);
            mma16816(acc0, a[2], pb[1][0], pb[1][1]);
            mma16816(acc1, a[3], pb[1][2], pb[1][3]);
            __syncwarp();
            if (lane == 0) mbar_arrive_cnt(bar_empty + stage * 8, 1);
            if (++stage == NSTAGE) { stage = 0; ph ^= 1u; }
        }
        st2(p, enc(acc0[0] + acc1[0], tag), enc(acc0[2] + acc1[2], tag));
        st2(p + 1024, enc(acc0[1] + acc1[1], tag), enc(acc0[3] + acc1[3], tag));
        bar_arrive(BAR_O, 320);
    }
    PROFW(0, 7);
    if (has_w1) {
        float acc0[4] = {0.f, 0.f, 0.f, 0.f}, acc1[4] = {0.f, 0.f, 0.f, 0.f};
        const uint32_t baddr = sbase + SM_YS + (g & 3) * YS_STRIDE + (kh2 * 64 + 2 * t) * 2;
#pragma unroll 1
        for (int j = 0; j < 4; j++) {
            mbar_wait(bar_full + stage * 8, ph, flag);
            gemv_tile4(acc0, acc1, sbase + stage * STAGE_BYTES + kh2 * 8192 + offT, baddr + j * 256, bvalid);
            ++stage;
        }
        float4* red = reinterpret_cast<float4*>(sptr + SM_RED + 1024) + mt * 16 + (g * 2 + (t & 1));
        if (kh2 == 1 && t < 2) *red = make_float4(acc0[0] + acc1[0], acc0[1] + acc1[1], acc0[2] + acc1[2], acc0[3] + acc1[3]);
        bar_sync(BAR_PAIR + mt, 64);
        if (kh2 == 0 && t < 2) {
            const float4 o = *red;
            unsigned int* p = g_h + (khalf * F_DIM + (c >> 1) * 64 + mt * 16 + g) * 4 + 2 * t;
            st2(p, enc(acc0[0] + acc1[0] + o.x, tag), enc(acc0[1] + acc1[1] + o.y, tag));
            st2(p + 32, enc(acc0[2] + acc1[2] + o.z, tag), enc(acc0[3] + acc1[3] + o.w, tag));
        }
    } else {
        mbar_wait(bar_full + stage * 8, ph, flag);
    }
    bar_arrive(BAR_W1, 288);
    PROFW(0, 3);
    const uint32_t offW0 = (warp >> 1) * 2048 + rowT + ((((uint32_t)(4 * (warp & 1) + ((lane >> 3) & 1))) ^ l8) << 4);
    const uint32_t offW1 = (warp >> 1) * 2048 + rowT + ((((uint32_t)(4 * (warp & 1) + 2 + ((lane >> 3) & 1))) ^ l8) << 4);
    {
        bar_sync(BAR_OS, 288);
        PROFW(0, 10);
        float acc0[4] = {0.f, 0.f, 0.f, 0.f}, acc1[4] = {0.f, 0.f, 0.f, 0.f};
        const uint32_t baddr = sbase + SM_OS + (g & 3) * FR_STRIDE + t * 8;
#pragma unroll 1
        for (int j = 0; j < 4; j++) {
            uint2 b0 = make_uint2(0u, 0u), b1 = make_uint2(0u, 0u);
            if (bvalid) { b0 = lds64(baddr + j * 64); b1 = lds64(baddr + j * 64 + 32); }
            mbar_wait(bar_full + stage * 8, ph, flag);
            const uint32_t base = sbase + stage * STAGE_BYTES;
            uint32_t a[4][4];
            ldsm_x4_t(a[0], base + offW0);
            ldsm_x4_t(a[1], base + offW1);
            ldsm_x4_t(a[2], base + 8192 + offW0);
            ldsm_x4_t(a[3], base + 8192 + offW1);
            mma16816(acc0, a[0], b0.x, b0.y);
            mma16816(acc1, a[1], b0.x, b0.y);
            mma16816(acc0, a[2], b1.x, b1.y);
            mma16816(acc1, a[3], b1.x, b1.y);
            ++stage;
        }
        if (t < 2) {
            unsigned int* p = g_a + dst_off;
            st2(p, enc(acc0[0], tag), enc(acc0[1], tag));
            st2(p + 1024, enc(acc0[2], tag), enc(acc0[3], tag));
            st2(p + 2048, enc(acc1[0], tag), enc(acc1[1], tag));
            st2(p + 3072, enc(acc1[2], tag), enc(acc1[3], tag));
        }
        bar_arrive(BAR_A, 288);
    }
    PROFW(0, 11);
    {
        bar_sync(BAR_HS, 288);
        PROFW(0, 8);
        float acc0[4] = {0.f, 0.f, 0.f, 0.f}, acc1[4] = {0.f, 0.f, 0.f, 0.f};
        const uint32_t baddr = sbase + SM_HS + (g & 3) * HS_STRIDE + t * 4;
#pragma unroll 1
        for (int j = 0; j < 3; j++) {
            uint32_t b[4] = {0u, 0u, 0u, 0u};
            if (bvalid) {
#pragma unroll
                for (int e = 0; e < 4; e++) b[e] = lds32(baddr + j * 64 + e * 16);
            }
            mbar_wait(bar_full + stage * 8, ph, flag);
            const uint32_t base = sbase + stage * STAGE_BYTES;
            uint32_t a[4][4];
            ldsm_x4_t(a[0], base + offW0);
            ldsm_x4_t(a[1], base + offW1);
            ldsm_x4_t(a[2], base + 8192 + offW0);
            ldsm_x4_t(a[3], base + 8192 + offW1);
            mma16816(acc0, a[0], b[0], b[1]);
            mma16816(acc1, a[1], b[0], b[1]);
            mma16816(acc0, a[2], b[2], b[3]);
            mma16816(acc1, a[3], b[2], b[3]);
            ++stage;
        }
        {
            uint32_t b0 = 0u, b1 = 0u;
            if (bvalid) { b0 = lds32(baddr + 192); b1 = lds32(baddr + 208); }
            mbar_wait(bar_full + stage * 8, ph, flag);
            const uint32_t base = sbase + stage * STAGE_BYTES;
            uint32_t a[2][4];
            ldsm_x4_t(a[0], base + offW0);
            ldsm_x4_t(a[1], base + offW1);
            mma16816(acc0, a[0], b0, b1);
            mma16816(acc1, a[1], b0, b1);
        }
        if (t < 2) {
            unsigned int* p = g_b + dst_off;
            st2(p, enc(acc0[0], tag), enc(acc0[1], tag));
            st2(p + 1024, enc(acc0[2], tag), enc(acc0[3], tag));
            st2(p + 2048, enc(acc1[0], tag), enc(acc1[1], tag));
            st2(p + 3072, enc(acc1[2], tag), enc(acc1[3], tag));
        }
        bar_arrive(BAR_B, 288);
    }
    PROFW(0, 9);
}

typedef CUresult (*EncodeFn)(CUtensorMap*, CUtensorMapDataType, cuuint32_t, void*, const cuuint64_t*, const cuuint64_t*,
                             const cuuint32_t*, const cuuint32_t*, CUtensorMapInterleave, CUtensorMapSwizzle,
                             CUtensorMapL2promotion, CUtensorMapFloatOOBfill);

void make_2d(EncodeFn enc_fn, CUtensorMap* tm, void* base, uint64_t cols, uint64_t rows, uint32_t box_rows) {
    cuuint64_t gd[2] = {cols, rows};
    cuuint64_t gs[1] = {cols * 2};
    cuuint32_t bd[2] = {64, box_rows};
    cuuint32_t es[2] = {1, 1};
    enc_fn(tm, CU_TENSOR_MAP_DATA_TYPE_BFLOAT16, 2, base, gd, gs, bd, es, CU_TENSOR_MAP_INTERLEAVE_NONE,
           CU_TENSOR_MAP_SWIZZLE_128B, CU_TENSOR_MAP_L2_PROMOTION_L2_128B, CU_TENSOR_MAP_FLOAT_OOB_FILL_NONE);
}
void make_3d(EncodeFn enc_fn, CUtensorMap* tm, void* base, uint64_t cols, uint64_t rows, uint32_t box_rows, uint32_t box_blocks) {
    cuuint64_t gd[3] = {64, rows, cols / 64};
    cuuint64_t gs[2] = {cols * 2, 128};
    cuuint32_t bd[3] = {64, box_rows, box_blocks};
    cuuint32_t es[3] = {1, 1, 1};
    enc_fn(tm, CU_TENSOR_MAP_DATA_TYPE_BFLOAT16, 3, base, gd, gs, bd, es, CU_TENSOR_MAP_INTERLEAVE_NONE,
           CU_TENSOR_MAP_SWIZZLE_128B, CU_TENSOR_MAP_L2_PROMOTION_L2_128B, CU_TENSOR_MAP_FLOAT_OOB_FILL_NONE);
}

}

extern "C" void kernel_launch(void* const* d_in, const int* in_sizes, int n_in, void* d_out, int out_size) {
    (void)in_sizes; (void)n_in; (void)out_size;
    static TMaps maps;
    static void* cached[6] = {nullptr, nullptr, nullptr, nullptr, nullptr, nullptr};
    static EncodeFn enc_fn = nullptr;
    if (!enc_fn) {
        void* fn = nullptr;
        cudaDriverEntryPointQueryResult qr;
        cudaGetDriverEntryPoint("cuTensorMapEncodeTiled", &fn, cudaEnableDefault, &qr);
        enc_fn = (EncodeFn)fn;
        cudaFuncSetAttribute(fused_kernel, cudaFuncAttributeMaxDynamicSharedMemorySize, SM_ALLOC);
    }
    void* cur[6] = {d_in[3], d_in[6], d_in[1], d_in[2], d_in[8], d_in[4]};
    bool same = true;
    for (int i = 0; i < 6; i++) same = same && (cur[i] == cached[i]);
    if (!same) {
        make_2d(enc_fn, &maps.wq, d_in[3], 4096, 1024, 128);
        make_2d(enc_fn, &maps.w1, d_in[6], F_DIM, 1024, 128);
        make_3d(enc_fn, &maps.k, d_in[1], 128, 16 * SK, 64, 2);
        make_3d(enc_fn, &maps.v, d_in[2], 128, 16 * SK, 64, 2);
        make_3d(enc_fn, &maps.w2, d_in[8], 1024, F_DIM, 16, 4);
        make_3d(enc_fn, &maps.wo, d_in[4], 1024, 4096, 16, 4);
        for (int i = 0; i < 6; i++) cached[i] = cur[i];
    }
    fused_kernel<<<NCTA, NTHREADS, SM_ALLOC, cudaStreamPerThread>>>(
        maps, (const __nv_bfloat16*)d_in[0], (const __nv_bfloat16*)d_in[7], (const __nv_bfloat16*)d_in[9],
        (const __nv_bfloat16*)d_in[10], (__nv_bfloat16*)d_out);
}
```

```cpp
#include <cuda_runtime.h>
#include <cuda.h>
#include <cuda_bf16.h>
#include <stdint.h>

namespace {

constexpr int NCTA = 128;
constexpr int NTHREADS = 416;
constexpr int NSTAGE = 12;
constexpr int STAGE_BYTES = 16384;

constexpr int D_MODEL = 1024;
constexpr int F_DIM = 3584;
constexpr int SK = 8192;

constexpr int SM_P = NSTAGE * STAGE_BYTES;
constexpr int SM_XS = SM_P;
constexpr int SM_YS = SM_P + 16384;
constexpr int SM_QS = SM_YS + 4160;
constexpr int SM_OS = SM_QS + 2304;
constexpr int SM_HS = SM_OS + 1152;
constexpr int SM_RED = SM_HS + 960;
constexpr int SM_MX = SM_RED + 2048;
constexpr int SM_LS = SM_MX + 256;
constexpr int SM_F = SM_LS + 256;
constexpr int SM_BAR = SM_F + 32;
constexpr int SM_FLAG = SM_BAR + 2 * NSTAGE * 8;
constexpr int SM_TOTAL = SM_FLAG + 8;
constexpr int SM_ALLOC = SM_TOTAL + 1024;

constexpr int XS_STRIDE = 1032 * 2;
constexpr int YS_STRIDE = 520 * 2;
constexpr int HS_STRIDE = 240;
constexpr int FR_STRIDE = 288;

#define PACE_T 660
#define PACE_LEAD 2
#define PACE_OFF PACE_T
#define PW_J 6
#define PACE_CAP 6
#define OG_DELAY 400

constexpr int BAR_INIT = 0;
constexpr int BAR_CONS = 1;
constexpr int BAR_PAIR = 2;
constexpr int BAR_X = 6;
constexpr int BAR_ML = 7;
constexpr int BAR_O = 8;
constexpr int BAR_OS = 9;
constexpr int BAR_W1 = 10;
constexpr int BAR_HS = 11;
constexpr int BAR_A = 12;
constexpr int BAR_B = 13;
constexpr int BAR_F = 14;

struct TMaps {
    CUtensorMap wq, w1, k, v, w2, wo;
};

constexpr int G_EPOCH = 0;
constexpr int G_Q = G_EPOCH + NCTA * 4;
constexpr int G_H = G_Q + 2 * 4 * 4096;
constexpr int G_ML = G_H + 2 * F_DIM * 4;
constexpr int G_O = G_ML + NCTA * 16;
constexpr int G_A = G_O + NCTA * 1024;
constexpr int G_B = G_A + NCTA * 1024;
constexpr int G_TOTAL = G_B + NCTA * 1024;
__device__ __align__(1024) unsigned int g_scratch[G_TOTAL];

#define PROF(i)
#define PROFW(w, i)
__device__ __forceinline__ uint32_t smem_u32(const void* p) { return (uint32_t)__cvta_generic_to_shared(p); }
__device__ __forceinline__ uint32_t gtime32() { uint32_t t; asm volatile("mov.u32 %0, %globaltimer_lo;" : "=r"(t)); return t; }

__device__ __forceinline__ void mbar_init(uint32_t bar, uint32_t cnt) {
    asm volatile("mbarrier.init.shared::cta.b64 [%0], %1;" ::"r"(bar), "r"(cnt) : "memory");
}
__device__ __forceinline__ void mbar_expect_tx(uint32_t bar, uint32_t bytes) {
    asm volatile("mbarrier.arrive.expect_tx.shared::cta.b64 _, [%0], %1;" ::"r"(bar), "r"(bytes) : "memory");
}
__device__ __forceinline__ void mbar_arrive_cnt(uint32_t bar, uint32_t cnt) {
    asm volatile("mbarrier.arrive.shared::cta.b64 _, [%0], %1;" ::"r"(bar), "r"(cnt) : "memory");
}
__device__ __forceinline__ bool mbar_try(uint32_t bar, uint32_t parity) {
    uint32_t ok;
    asm volatile(
        "{\n.reg .pred p;\n"
        "mbarrier.try_wait.parity.shared::cta.b64 p, [%1], %2;\n"
        "selp.u32 %0, 1, 0, p;\n}\n"
        : "=r"(ok)
        : "r"(bar), "r"(parity)
        : "memory");
    return ok != 0;
}
__device__ __noinline__ void mbar_wait_slow(uint32_t bar, uint32_t parity, volatile uint32_t* flag) {
    long long t0 = clock64();
    for (uint32_t it = 0; it < 0x40000000u; it++) {
        if (mbar_try(bar, parity)) return;
        if ((it & 63u) == 63u) {
            if (*flag) return;
            if (clock64() - t0 > 2000000000LL) { *flag = 1u; return; }
        }
    }
}
__device__ __forceinline__ void mbar_wait(uint32_t bar, uint32_t parity, volatile uint32_t* flag) {
    if (mbar_try(bar, parity)) return;
    if (mbar_try(bar, parity)) return;
    mbar_wait_slow(bar, parity, flag);
}

__device__ __forceinline__ void tma_2d(uint32_t dst, const CUtensorMap* tm, int c0, int c1, uint32_t bar) {
    asm volatile(
        "cp.async.bulk.tensor.2d.shared::cluster.global.mbarrier::complete_tx::bytes.L2::cache_hint [%0], [%1, {%3, %4}], [%2], %5;"
        ::"r"(dst), "l"(tm), "r"(bar), "r"(c0), "r"(c1), "l"(0x12F0000000000000ull)
        : "memory");
}
__device__ __forceinline__ void tma_3d(uint32_t dst, const CUtensorMap* tm, int c0, int c1, int c2, uint32_t bar) {
    asm volatile(
        "cp.async.bulk.tensor.3d.shared::cluster.global.mbarrier::complete_tx::bytes.L2::cache_hint [%0], [%1, {%3, %4, %5}], [%2], %6;"
        ::"r"(dst), "l"(tm), "r"(bar), "r"(c0), "r"(c1), "r"(c2), "l"(0x12F0000000000000ull)
        : "memory");
}
__device__ __forceinline__ void bulk_load(uint32_t dst, const void* src, uint32_t bytes, uint32_t bar) {
    asm volatile("cp.async.bulk.shared::cluster.global.mbarrier::complete_tx::bytes [%0], [%1], %2, [%3];"
                 ::"r"(dst), "l"(src), "r"(bytes), "r"(bar)
                 : "memory");
}
__device__ __forceinline__ void prefetch_tmap(const CUtensorMap* tm) {
    asm volatile("prefetch.tensormap [%0];" ::"l"(tm) : "memory");
}
__device__ __forceinline__ void bar_sync(int id, int cnt) { asm volatile("bar.sync %0, %1;" ::"r"(id), "r"(cnt) : "memory"); }
__device__ __forceinline__ void bar_arrive(int id, int cnt) { asm volatile("bar.arrive %0, %1;" ::"r"(id), "r"(cnt) : "memory"); }

__device__ __forceinline__ void ldsm_x4(uint32_t (&r)[4], uint32_t addr) {
    asm volatile("ldmatrix.sync.aligned.m8n8.x4.shared.b16 {%0,%1,%2,%3}, [%4];"
                 : "=r"(r[0]), "=r"(r[1]), "=r"(r[2]), "=r"(r[3])
                 : "r"(addr)
                 : "memory");
}
__device__ __forceinline__ void ldsm_x4_t(uint32_t (&r)[4], uint32_t addr) {
    asm volatile("ldmatrix.sync.aligned.m8n8.x4.trans.shared.b16 {%0,%1,%2,%3}, [%4];"
                 : "=r"(r[0]), "=r"(r[1]), "=r"(r[2]), "=r"(r[3])
                 : "r"(addr)
                 : "memory");
}
__device__ __forceinline__ void mma16816(float (&c)[4], const uint32_t (&a)[4], uint32_t b0, uint32_t b1) {
    asm volatile(
        "mma.sync.aligned.m16n8k16.row.col.f32.bf16.bf16.f32 {%0,%1,%2,%3}, {%4,%5,%6,%7}, {%8,%9}, {%0,%1,%2,%3};"
        : "+f"(c[0]), "+f"(c[1]), "+f"(c[2]), "+f"(c[3])
        : "r"(a[0]), "r"(a[1]), "r"(a[2]), "r"(a[3]), "r"(b0), "r"(b1));
}
__device__ __forceinline__ uint32_t lds32(uint32_t addr) {
    uint32_t v;
    asm volatile("ld.shared.b32 %0, [%1];" : "=r"(v) : "r"(addr) : "memory");
    return v;
}
__device__ __forceinline__ uint2 lds64(uint32_t addr) {
    uint2 v;
    asm volatile("ld.shared.v2.b32 {%0, %1}, [%2];" : "=r"(v.x), "=r"(v.y) : "r"(addr) : "memory");
    return v;
}
__device__ __forceinline__ void sts32(uint32_t addr, uint32_t v) {
    asm volatile("st.shared.b32 [%0], %1;" ::"r"(addr), "r"(v) : "memory");
}
__device__ __forceinline__ void sts64(uint32_t addr, uint32_t a, uint32_t b) {
    asm volatile("st.shared.v2.b32 [%0], {%1, %2};" ::"r"(addr), "r"(a), "r"(b) : "memory");
}

__device__ __forceinline__ float bf16r(float x) { return __bfloat162float(__float2bfloat16_rn(x)); }
__device__ __forceinline__ uint32_t pack_bf16(float lo, float hi) {
    __nv_bfloat162 v = __floats2bfloat162_rn(lo, hi);
    return *reinterpret_cast<uint32_t*>(&v);
}
__device__ __forceinline__ float bf_lo(uint32_t u) { return __uint_as_float(u << 16); }
__device__ __forceinline__ float bf_hi(uint32_t u) { return __uint_as_float(u & 0xffff0000u); }

__device__ __forceinline__ uint32_t enc(float v, uint32_t tag) { return (__float_as_uint(v) & ~3u) | tag; }
__device__ __forceinline__ float dec(uint32_t u) { return __uint_as_float(u & ~3u); }
__device__ __forceinline__ void st2(unsigned int* p, uint32_t a, uint32_t b) {
    asm volatile("st.relaxed.gpu.global.v2.b32 [%0], {%1, %2};" ::"l"(p), "r"(a), "r"(b) : "memory");
}
__device__ __forceinline__ void st4(unsigned int* p, uint32_t a, uint32_t b, uint32_t c, uint32_t d) {
    asm volatile("st.relaxed.gpu.global.v4.b32 [%0], {%1, %2, %3, %4};" ::"l"(p), "r"(a), "r"(b), "r"(c), "r"(d) : "memory");
}
__device__ __forceinline__ uint32_t ld1(const unsigned int* p) {
    uint32_t v;
    asm volatile("ld.relaxed.gpu.global.b32 %0, [%1];" : "=r"(v) : "l"(p) : "memory");
    return v;
}
__device__ __forceinline__ uint2 ld2(const unsigned int* p) {
    uint2 v;
    asm volatile("ld.relaxed.gpu.global.v2.b32 {%0, %1}, [%2];" : "=r"(v.x), "=r"(v.y) : "l"(p) : "memory");
    return v;
}
__device__ __forceinline__ uint4 ld4(const unsigned int* p) {
    uint4 v;
    asm volatile("ld.relaxed.gpu.global.v4.b32 {%0, %1, %2, %3}, [%4];" : "=r"(v.x), "=r"(v.y), "=r"(v.z), "=r"(v.w) : "l"(p) : "memory");
    return v;
}
__device__ __forceinline__ uint32_t bad4(const uint4& v, uint32_t tag) { return (v.x ^ tag) | (v.y ^ tag) | (v.z ^ tag) | (v.w ^ tag); }
__device__ __forceinline__ bool warp_ok(uint32_t bad) { return __all_sync(0xffffffffu, (bad & 3u) == 0u); }
constexpr uint32_t POLL_LIMIT = 1u << 21;

__device__ __forceinline__ void gemv_tile4(float (&acc0)[4], float (&acc1)[4], uint32_t a_addr, uint32_t b_addr, bool bvalid) {
    uint32_t a[4][4];
    uint32_t b[4][2];
#pragma unroll
    for (int ks = 0; ks < 4; ks++) ldsm_x4_t(a[ks], a_addr + ks * 2048);
#pragma unroll
    for (int ks = 0; ks < 4; ks++) {
        b[ks][0] = bvalid ? lds32(b_addr + ks * 32) : 0u;
        b[ks][1] = bvalid ? lds32(b_addr + ks * 32 + 16) : 0u;
    }
#pragma unroll
    for (int ks = 0; ks < 4; ks++) {
        if (ks & 1) mma16816(acc1, a[ks], b[ks][0], b[ks][1]);
        else mma16816(acc0, a[ks], b[ks][0], b[ks][1]);
    }
}

__device__ __forceinline__ float final_sum(const unsigned int* buf, int lane, uint32_t tag, bool backoff) {
    const unsigned int* p = buf + (lane >> 3) * 256 + (lane & 7) * 4;
    uint4 d[8];
    for (uint32_t it = 0; it < POLL_LIMIT; it++) {
        uint32_t bad = 0;
#pragma unroll
        for (int i = 0; i < 8; i++) { d[i] = ld4(p + i * 32); bad |= bad4(d[i], tag); }
        if (warp_ok(bad)) break;
        if (backoff) __nanosleep(100);
    }
    float s0 = 0.f, s1 = 0.f, s2 = 0.f, s3 = 0.f;
#pragma unroll
    for (int i = 0; i < 8; i++) { s0 += dec(d[i].x); s1 += dec(d[i].y); s2 += dec(d[i].z); s3 += dec(d[i].w); }
    const bool hi = lane & 16;
    float u0 = hi ? s0 : s2, u1 = hi ? s1 : s3;
    float k0 = hi ? s2 : s0, k1 = hi ? s3 : s1;
    k0 += __shfl_xor_sync(0xffffffffu, u0, 16);
    k1 += __shfl_xor_sync(0xffffffffu, u1, 16);
    const bool od = lane & 8;
    const float w = od ? k0 : k1;
    float r = od ? k1 : k0;
    r += __shfl_xor_sync(0xffffffffu, w, 8);
    return r;
}

__global__ void __launch_bounds__(NTHREADS, 1)
fused_kernel(const __nv_bfloat16* __restrict__ wq, const __nv_bfloat16* __restrict__ x, unsigned int* __restrict__ scr,
             __nv_bfloat16* __restrict__ out, const __nv_bfloat16* __restrict__ gate_w, const __nv_bfloat16* __restrict__ b1,
             const __grid_constant__ TMaps maps, const __nv_bfloat16* __restrict__ b2) {
    extern __shared__ unsigned char smem_raw[];
    const uint32_t sbase = (smem_u32(smem_raw) + 1023u) & ~1023u;
    unsigned char* sptr = smem_raw + (sbase - smem_u32(smem_raw));
    volatile uint32_t* flag = reinterpret_cast<volatile uint32_t*>(sptr + SM_FLAG);

    const int c = blockIdx.x;
    const int tid = threadIdx.x;
    const int warp = tid >> 5;
    const int lane = tid & 31;
    const bool has_w1 = c < 112;
    const int kb = c >> 2, nb = c & 3;
    const uint32_t bar_full = sbase + SM_BAR;
    const uint32_t bar_empty = sbase + SM_BAR + NSTAGE * 8;

    PROFW(0, 0);
    if (warp == 8) {
        const int n_w1 = has_w1 ? 4 : 0;
        const int n_tiles = 44 + n_w1;
        const int kv_row0 = (c >> 3) * SK + (c & 7) * 1024;
        uint32_t due = 0;
        if (lane == 0) {
#pragma unroll
            for (int j = 0; j < PACE_LEAD; j++) mbar_init(bar_full + j * 8, 1);
            asm volatile("fence.mbarrier_init.release.cluster;" ::: "memory");
            asm volatile("fence.proxy.async.shared::cta;" ::: "memory");
#pragma unroll
            for (int j = 0; j < PACE_LEAD; j++) {
                mbar_expect_tx(bar_full + j * 8, STAGE_BYTES);
                tma_2d(sbase + j * STAGE_BYTES, &maps.wq, (c >> 1) * 64, (c & 1) * 512 + j * 128, bar_full + j * 8);
            }
            due = gtime32() + PACE_OFF + (c >> 1) * PACE_T / 64;
#pragma unroll
            for (int i = PACE_LEAD; i < NSTAGE; i++) mbar_init(bar_full + i * 8, 1);
#pragma unroll
            for (int i = 0; i < NSTAGE; i++) mbar_init(bar_empty + i * 8, 8);
            *flag = 0u;
            asm volatile("fence.mbarrier_init.release.cluster;" ::: "memory");
            asm volatile("fence.proxy.async.shared::cta;" ::: "memory");
            prefetch_tmap(&maps.w1);
            prefetch_tmap(&maps.k);
            prefetch_tmap(&maps.v);
            prefetch_tmap(&maps.w2);
            prefetch_tmap(&maps.wo);
        }
        __syncwarp();
        bar_arrive(BAR_INIT, NTHREADS);
        if (lane == 0) {
            int landed = 0;
            for (int i = PACE_LEAD; i < n_tiles; i++) {
                while (landed + PACE_CAP <= i) {
                    mbar_wait(bar_full + (landed % NSTAGE) * 8, (uint32_t)(landed / NSTAGE) & 1u, flag);
                    landed++;
                }
                const int stage = i % NSTAGE;
                if (i >= NSTAGE) mbar_wait(bar_empty + stage * 8, (uint32_t)(i / NSTAGE - 1) & 1u, flag);
                for (int it = 0; it < 100000 && (int)(gtime32() - due) < 0; it++) {}
                const uint32_t dst = sbase + stage * STAGE_BYTES;
                const uint32_t fb = bar_full + stage * 8;
                int j = i - 4;
                if (j < 0) {
                    mbar_expect_tx(fb, STAGE_BYTES);
                    tma_2d(dst, &maps.wq, (c >> 1) * 64, (c & 1) * 512 + i * 128, fb);
                    due += (j == -1 && !has_w1) ? PACE_T * 9 / 2 : PACE_T;
                } else if (j < n_w1) {
                    mbar_expect_tx(fb, STAGE_BYTES);
                    tma_2d(dst, &maps.w1, (c >> 1) * 64, (c & 1) * 512 + j * 128, fb);
                    due += PACE_T * 7 / 8;
                } else if (j < 32 + n_w1) {
                    j -= n_w1;
                    mbar_expect_tx(fb, STAGE_BYTES);
                    tma_3d(dst, j < 16 ? &maps.k : &maps.v, 0, kv_row0 + (j & 15) * 64, 0, fb);
                    due += PACE_T;
                } else {
                    j -= 32 + n_w1;
                    const CUtensorMap* tm = j < 4 ? &maps.w2 : &maps.wo;
                    const int row = j < 4 ? kb * 112 + j * 32 : kb * 128 + (j - 4) * 32;
                    mbar_expect_tx(fb, j != 3 ? STAGE_BYTES : STAGE_BYTES / 2);
                    tma_3d(dst, tm, 0, row, nb * 4, fb);
                    if (j != 3) tma_3d(dst + 8192, tm, 0, row + 16, nb * 4, fb);
                    due += j != 3 ? PACE_T : PACE_T / 2;
                }
            }
            PROF(20);
        }
        return;
    }

    const int g = lane >> 2;
    const int t = lane & 3;
    const int khalf = c & 1;
    const int pair = c >> 3;
    const int mt = warp & 3;
    const int kh2 = warp >> 2;
    const uint32_t epoch = ld1(scr + G_EPOCH + c * 4) + 1u;
    unsigned int* const q_dst = scr + G_Q + (khalf * 4 + 2 * t) * 4096 + (c >> 1) * 64 + mt * 16 + 2 * g;
    unsigned int* const h_dst = scr + G_H + (khalf * F_DIM + (c >> 1) * 64 + mt * 16 + g) * 4 + 2 * t;
    if (warp < 8) {
        asm volatile("prefetch.global.L2 [%0];" ::"l"(wq + (size_t)(khalf * 512 + tid) * 4096 + (c >> 1) * 64));
        const uint4 x0 = __ldg(reinterpret_cast<const uint4*>(x) + tid);
        const uint4 x1 = __ldg(reinterpret_cast<const uint4*>(x) + 256 + tid);
        if (warp < 4 && t < 2) {
            st2(q_dst, 0u, 0u);
            st2(q_dst + 4096, 0u, 0u);
            if (has_w1) {
                st2(h_dst, 0u, 0u);
                st2(h_dst + 32, 0u, 0u);
            }
        }
        *reinterpret_cast<uint4*>(sptr + SM_XS + (tid >> 7) * XS_STRIDE + (tid & 127) * 16) = x0;
        *reinterpret_cast<uint4*>(sptr + SM_XS + (2 + (tid >> 7)) * XS_STRIDE + (tid & 127) * 16) = x1;
    }
    const uint32_t tag = 1u + epoch % 3u;

    if (warp >= 9) {
        float gate = 0.f, b2v = 0.f;
        if (warp == 9) {
            uint4 gw[4];
#pragma unroll
            for (int i = 0; i < 4; i++) gw[i] = __ldg(reinterpret_cast<const uint4*>(gate_w) + i * 32 + lane);
            b2v = __bfloat162float(b2[c * 8 + (lane & 7)]);
            bar_sync(BAR_INIT, NTHREADS);
            float zz = 0.f;
#pragma unroll 1
            for (int b = 0; b < 4; b++) {
                float zs = 0.f;
#pragma unroll
                for (int i = 0; i < 4; i++) {
                    const uint4 xv = *reinterpret_cast<const uint4*>(sptr + SM_XS + b * XS_STRIDE + (i * 32 + lane) * 16);
                    const uint32_t xa[4] = {xv.x, xv.y, xv.z, xv.w};
                    const uint32_t wa[4] = {gw[i].x, gw[i].y, gw[i].z, gw[i].w};
#pragma unroll
                    for (int e = 0; e < 4; e++) {
                        zs += bf16r(bf_lo(xa[e]) * bf_lo(wa[e]));
                        zs += bf16r(bf_hi(xa[e]) * bf_hi(wa[e]));
                    }
                }
#pragma unroll
                for (int o = 16; o > 0; o >>= 1) zs += __shfl_xor_sync(0xffffffffu, zs, o);
                if ((lane >> 3) == b) zz = zs;
            }
            bar_arrive(BAR_X, 288);
            zz = bf16r(zz);
            gate = bf16r(1.0f / (1.0f + __expf(-zz)));
            PROF(12);
        } else if (warp == 11) {
            const bool has4 = lane < 16;
            float bias[4];
#pragma unroll
            for (int i = 0; i < 4; i++) bias[i] = (i < 3 || has4) ? __bfloat162float(b1[kb * 112 + i * 32 + lane]) : 0.f;
            bar_sync(BAR_INIT, NTHREADS);
            bar_sync(BAR_W1, 288);
            const unsigned int* p = scr + G_H + (kb * 112 + lane) * 4;
            uint4 d[4][2];
            for (uint32_t it = 0; it < POLL_LIMIT; it++) {
                __nanosleep(1000);
                uint32_t bad = 0;
#pragma unroll
                for (int i = 0; i < 4; i++) {
                    if (i < 3 || has4) {
                        d[i][0] = ld4(p + i * 128);
                        d[i][1] = ld4(p + i * 128 + F_DIM * 4);
                        bad |= bad4(d[i][0], tag) | bad4(d[i][1], tag);
                    }
                }
                if (warp_ok(bad)) break;
            }
            PROF(16);
#pragma unroll
            for (int i = 0; i < 4; i++) {
                if (i < 3 || has4) {
                    const int cl = i * 32 + lane;
                    const uint32_t u0[4] = {d[i][0].x, d[i][0].y, d[i][0].z, d[i][0].w};
                    const uint32_t u1[4] = {d[i][1].x, d[i][1].y, d[i][1].z, d[i][1].w};
#pragma unroll
                    for (int b = 0; b < 4; b++) {
                        float v = bf16r(dec(u0[b]) + dec(u1[b]));
                        v = bf16r(v + bias[i]);
                        const float inner = 0.7978845608028654f * (v + 0.044715f * v * v * v);
                        const float hv = 0.5f * v * (1.0f + tanhf(inner));
                        *reinterpret_cast<__nv_bfloat16*>(sptr + SM_HS + b * HS_STRIDE + cl * 2) = __float2bfloat16_rn(hv);
                    }
                }
            }
            bar_arrive(BAR_HS, 288);
            PROF(18);
        } else if (warp == 12) {
            bar_sync(BAR_INIT, NTHREADS);
            bar_sync(BAR_ML, 64);
            const unsigned int* p = scr + G_ML + pair * 128 + lane * 4;
            uint4 d;
            for (uint32_t it = 0; it < POLL_LIMIT; it++) {
                __nanosleep(1000);
                d = ld4(p);
                if (warp_ok(bad4(d, tag))) break;
            }
            const float m0 = dec(d.x), m1 = dec(d.z);
            float M0 = m0, M1 = m1;
#pragma unroll
            for (int o = 4; o < 32; o <<= 1) {
                M0 = fmaxf(M0, __shfl_xor_sync(0xffffffffu, M0, o));
                M1 = fmaxf(M1, __shfl_xor_sync(0xffffffffu, M1, o));
            }
            const float w0 = exp2f((m0 - M0) * 1.4426950408889634f), w1 = exp2f((m1 - M1) * 1.4426950408889634f);
            float L0 = w0 * dec(d.y), L1 = w1 * dec(d.w);
#pragma unroll
            for (int o = 4; o < 32; o <<= 1) {
                L0 += __shfl_xor_sync(0xffffffffu, L0, o);
                L1 += __shfl_xor_sync(0xffffffffu, L1, o);
            }
            if (g == (c & 7)) *reinterpret_cast<float2*>(sptr + SM_F + t * 8) = make_float2(w0 / L0, w1 / L1);
            bar_arrive(BAR_F, 288);
            PROF(13);
        } else {
            bar_sync(BAR_INIT, NTHREADS);
        }
        {
            const int hb = warp - 9;
            const unsigned int* po = scr + G_O + ((hb * 4 + (kb >> 3)) * 8 + (kb & 7)) * 1024 + lane * 4;
            uint4 d[8];
            uint32_t pend = 0xffu;
            bar_sync(BAR_O, 384);
            __nanosleep(OG_DELAY);
            for (uint32_t it = 0; it < POLL_LIMIT; it++) {
#pragma unroll
                for (int s = 0; s < 8; s++)
                    if (pend & (1u << s)) d[s] = ld4(po + s * 128);
#pragma unroll
                for (int s = 0; s < 8; s++)
                    if ((pend & (1u << s)) && warp_ok(bad4(d[s], tag))) pend &= ~(1u << s);
                if (pend == 0u) break;
                __nanosleep(100);
            }
            float o0 = 0.f, o1 = 0.f, o2 = 0.f, o3 = 0.f;
#pragma unroll
            for (int s = 0; s < 8; s++) {
                o0 += dec(d[s].x);
                o1 += dec(d[s].y);
                o2 += dec(d[s].z);
                o3 += dec(d[s].w);
            }
            sts64(sbase + SM_OS + hb * FR_STRIDE + lane * 8, pack_bf16(o0, o2), pack_bf16(o1, o3));
            bar_arrive(BAR_OS, 384);
        }
        if (warp != 9) return;
        PROF(14);
        bar_sync(BAR_B, 288);
        const float bv = bf16r(bf16r(final_sum(scr + G_B + c * 1024, lane, tag, true)) + b2v);
        const float bterm = bf16r(bf16r(1.0f - gate) * bv);
        PROF(17);
        bar_sync(BAR_A, 288);
        const float aterm = bf16r(gate * bf16r(final_sum(scr + G_A + c * 1024, lane, tag, false)));
        out[(lane >> 3) * D_MODEL + c * 8 + (lane & 7)] = __float2bfloat16_rn(aterm + bterm);
        PROF(19);
        if (lane == 0) *reinterpret_cast<volatile unsigned int*>(scr + G_EPOCH + c * 4) = epoch;
        return;
    }

    bar_sync(BAR_INIT, NTHREADS);
    PROFW(0, 1);

    int stage = 0;
    uint32_t ph = 0;
    const uint32_t l8 = lane & 7;
    const uint32_t rowT = (l8 + 8 * (lane >> 4)) * 128;
    const uint32_t offT = rowT + ((((uint32_t)(2 * mt + ((lane >> 3) & 1))) ^ l8) << 4);
    const bool bvalid = g < 4;
    const int dst_off = ((nb * 32 + warp * 4) * 32 + kb) * 32 + g * 4 + 2 * t;

    {
        float acc0[4] = {0.f, 0.f, 0.f, 0.f}, acc1[4] = {0.f, 0.f, 0.f, 0.f};
        const uint32_t baddr = sbase + SM_XS + (g & 3) * XS_STRIDE + (khalf * 512 + kh2 * 64 + 2 * t) * 2;
#pragma unroll 1
        for (int j = 0; j < 4; j++) {
            mbar_wait(bar_full + stage * 8, ph, flag);
            gemv_tile4(acc0, acc1, sbase + stage * STAGE_BYTES + kh2 * 8192 + offT, baddr + j * 256, bvalid);
            __syncwarp();
            if (lane == 0) mbar_arrive_cnt(bar_empty + stage * 8, 1);
            ++stage;
        }
        float4* red = reinterpret_cast<float4*>(sptr + SM_RED) + mt * 16 + (g * 2 + (t & 1));
        if (kh2 == 1 && t < 2) *red = make_float4(acc0[0] + acc1[0], acc0[1] + acc1[1], acc0[2] + acc1[2], acc0[3] + acc1[3]);
        bar_sync(BAR_PAIR + mt, 64);
        if (kh2 == 0 && t < 2) {
            const float4 o = *red;
            st2(q_dst, enc(acc0[0] + acc1[0] + o.x, tag), enc(acc0[2] + acc1[2] + o.z, tag));
            st2(q_dst + 4096, enc(acc0[1] + acc1[1] + o.y, tag), enc(acc0[3] + acc1[3] + o.w, tag));
        }
    }
    PROFW(0, 2);
    if (has_w1) {
        {
            uint4 xv[4];
#pragma unroll
            for (int i = 0; i < 4; i++) xv[i] = *reinterpret_cast<const uint4*>(sptr + SM_XS + mt * XS_STRIDE + (i * 32 + lane) * 16);
            const uint4 xs = *reinterpret_cast<const uint4*>(sptr + SM_XS + mt * XS_STRIDE + (khalf * 64 + kh2 * 32 + lane) * 16);
            float s0 = 0.f, s1 = 0.f;
#pragma unroll
            for (int i = 0; i < 4; i++) {
                const uint32_t xa[4] = {xv[i].x, xv[i].y, xv[i].z, xv[i].w};
#pragma unroll
                for (int e = 0; e < 4; e++) { s0 += bf_lo(xa[e]); s1 += bf_hi(xa[e]); }
            }
            float s = s0 + s1;
#pragma unroll
            for (int o = 16; o > 0; o >>= 1) s += __shfl_xor_sync(0xffffffffu, s, o);
            const float mean = s * (1.0f / 1024.0f);
            float q0 = 0.f, q1 = 0.f;
#pragma unroll
            for (int i = 0; i < 4; i++) {
                const uint32_t xa[4] = {xv[i].x, xv[i].y, xv[i].z, xv[i].w};
#pragma unroll
                for (int e = 0; e < 4; e++) {
                    const float d0 = bf_lo(xa[e]) - mean, d1 = bf_hi(xa[e]) - mean;
                    q0 = fmaf(d0, d0, q0);
                    q1 = fmaf(d1, d1, q1);
                }
            }
            float q = q0 + q1;
#pragma unroll
            for (int o = 16; o > 0; o >>= 1) q += __shfl_xor_sync(0xffffffffu, q, o);
            const float mb = bf16r(mean);
            const float vb = bf16r(q * (1.0f / 1024.0f));
            const float den = bf16r(sqrtf(bf16r(vb + 1e-5f)));
            const uint32_t xa[4] = {xs.x, xs.y, xs.z, xs.w};
            uint32_t ya[4];
#pragma unroll
            for (int e = 0; e < 4; e++) ya[e] = pack_bf16(bf16r(bf_lo(xa[e]) - mb) / den, bf16r(bf_hi(xa[e]) - mb) / den);
            *reinterpret_cast<uint4*>(sptr + SM_YS + mt * YS_STRIDE + (kh2 * 32 + lane) * 16) = make_uint4(ya[0], ya[1], ya[2], ya[3]);
            bar_sync(BAR_CONS, 256);
        }
        float acc0[4] = {0.f, 0.f, 0.f, 0.f}, acc1[4] = {0.f, 0.f, 0.f, 0.f};
        const uint32_t baddr = sbase + SM_YS + (g & 3) * YS_STRIDE + (kh2 * 64 + 2 * t) * 2;
#pragma unroll 1
        for (int j = 0; j < 4; j++) {
            mbar_wait(bar_full + stage * 8, ph, flag);
            gemv_tile4(acc0, acc1, sbase + stage * STAGE_BYTES + kh2 * 8192 + offT, baddr + j * 256, bvalid);
            __syncwarp();
            if (lane == 0) mbar_arrive_cnt(bar_empty + stage * 8, 1);
            ++stage;
        }
        float4* red = reinterpret_cast<float4*>(sptr + SM_RED + 1024) + mt * 16 + (g * 2 + (t & 1));
        if (kh2 == 1 && t < 2) *red = make_float4(acc0[0] + acc1[0], acc0[1] + acc1[1], acc0[2] + acc1[2], acc0[3] + acc1[3]);
        bar_sync(BAR_PAIR + mt, 64);
        if (kh2 == 0 && t < 2) {
            const float4 o = *red;
            st2(h_dst, enc(acc0[0] + acc1[0] + o.x, tag), enc(acc0[1] + acc1[1] + o.y, tag));
            st2(h_dst + 32, enc(acc0[2] + acc1[2] + o.z, tag), enc(acc0[3] + acc1[3] + o.w, tag));
        }
    } else {
        mbar_wait(bar_full + stage * 8, ph, flag);
    }
    bar_arrive(BAR_W1, 288);
    PROFW(0, 3);
    uint32_t qf[8][2];
    {
        const unsigned int* p = scr + G_Q + (pair >> 2) * 4096 + (pair & 3) * 1024 + tid * 4;
        uint4 d0, d1;
        for (uint32_t it = 0; it < POLL_LIMIT; it++) {
            d0 = ld4(p);
            d1 = ld4(p + 4 * 4096);
            if (warp_ok(bad4(d0, tag) | bad4(d1, tag))) break;
            __nanosleep(200);
        }
        sts64(sbase + SM_QS + warp * FR_STRIDE + lane * 8,
              pack_bf16(dec(d0.x) + dec(d1.x), dec(d0.z) + dec(d1.z)), pack_bf16(dec(d0.y) + dec(d1.y), dec(d0.w) + dec(d1.w)));
        bar_sync(BAR_CONS, 256);
#pragma unroll
        for (int ks = 0; ks < 8; ks++) {
            const uint2 v = lds64(sbase + SM_QS + g * FR_STRIDE + (ks * 4 + t) * 8);
            qf[ks][0] = v.x;
            qf[ks][1] = v.y;
        }
    }
    PROFW(0, 4);
    float sc[8][4];
    {
        int st = stage + kh2;
        uint32_t php = ph;
        const uint32_t krow = mt * 16 + l8 + 8 * ((lane >> 3) & 1);
        const uint32_t khi = lane >> 4;
#pragma unroll
        for (int i = 0; i < 8; i++) {
            mbar_wait(bar_full + st * 8, php, flag);
            const uint32_t base = sbase + st * STAGE_BYTES + krow * 128;
            float c0[4] = {0.f, 0.f, 0.f, 0.f}, c1[4] = {0.f, 0.f, 0.f, 0.f};
            uint32_t a[8][4];
#pragma unroll
            for (int ks = 0; ks < 8; ks++)
                ldsm_x4(a[ks], base + (ks >> 2) * 8192 + (((uint32_t)((ks & 3) * 2) + khi) ^ l8) * 16);
#pragma unroll
            for (int ks = 0; ks < 8; ks++) {
                if (ks & 1) mma16816(c1, a[ks], qf[ks][0], qf[ks][1]);
                else mma16816(c0, a[ks], qf[ks][0], qf[ks][1]);
            }
            __syncwarp();
            if (lane == 0) mbar_arrive_cnt(bar_empty + st * 8, 2);
#pragma unroll
            for (int e = 0; e < 4; e++) sc[i][e] = bf16r(bf16r(c0[e] + c1[e]) * 0.08838834764831845f);
            st += 2;
            if (st >= NSTAGE) { st -= NSTAGE; php ^= 1u; }
        }
        stage += 16 - NSTAGE;
        ph ^= 1u;
        if (stage >= NSTAGE) { stage -= NSTAGE; ph ^= 1u; }
    }
    PROFW(0, 5);
    {
        float m0 = sc[0][0], m1 = sc[0][1];
#pragma unroll
        for (int i = 0; i < 8; i++) {
            m0 = fmaxf(m0, fmaxf(sc[i][0], sc[i][2]));
            m1 = fmaxf(m1, fmaxf(sc[i][1], sc[i][3]));
        }
#pragma unroll
        for (int o = 4; o < 32; o <<= 1) {
            m0 = fmaxf(m0, __shfl_xor_sync(0xffffffffu, m0, o));
            m1 = fmaxf(m1, __shfl_xor_sync(0xffffffffu, m1, o));
        }
        float2* mx = reinterpret_cast<float2*>(sptr + SM_MX);
        if (g == 0) mx[warp * 4 + t] = make_float2(m0, m1);
        bar_sync(BAR_X, 288);
#pragma unroll
        for (int w = 0; w < 8; w++) {
            const float2 v = mx[w * 4 + t];
            m0 = fmaxf(m0, v.x);
            m1 = fmaxf(m1, v.y);
        }
        float l0 = 0.f, l1 = 0.f;
#pragma unroll
        for (int i = 0; i < 8; i++) {
            const float e0 = exp2f((sc[i][0] - m0) * 1.4426950408889634f);
            const float e1 = exp2f((sc[i][1] - m1) * 1.4426950408889634f);
            const float e2 = exp2f((sc[i][2] - m0) * 1.4426950408889634f);
            const float e3 = exp2f((sc[i][3] - m1) * 1.4426950408889634f);
            l0 += e0 + e2;
            l1 += e1 + e3;
            const uint32_t key = (2 * i + kh2) * 64 + mt * 16 + g;
            sts32(sbase + SM_P + key * 16 + t * 4, pack_bf16(e0, e1));
            sts32(sbase + SM_P + (key + 8) * 16 + t * 4, pack_bf16(e2, e3));
        }
#pragma unroll
        for (int o = 4; o < 32; o <<= 1) {
            l0 += __shfl_xor_sync(0xffffffffu, l0, o);
            l1 += __shfl_xor_sync(0xffffffffu, l1, o);
        }
        float2* ls = reinterpret_cast<float2*>(sptr + SM_LS);
        if (g == 0) ls[warp * 4 + t] = make_float2(l0, l1);
        bar_sync(BAR_CONS, 256);
        if (warp == 0) {
            l0 = 0.f;
            l1 = 0.f;
#pragma unroll
            for (int w = 0; w < 8; w++) {
                const float2 v = ls[w * 4 + t];
                l0 += v.x;
                l1 += v.y;
            }
            if (g == 0) st4(scr + G_ML + c * 16 + t * 4, enc(m0, tag), enc(l0, tag), enc(m1, tag), enc(l1, tag));
            bar_arrive(BAR_ML, 64);
        }
    }
    PROFW(0, 6);
    {
        float acc0[4] = {0.f, 0.f, 0.f, 0.f}, acc1[4] = {0.f, 0.f, 0.f, 0.f};
        const uint32_t paddr = sbase + SM_P + lane * 16;
        unsigned int* p = scr + G_O + ((pair * 8 + 2 * t) * 8 + (c & 7)) * 128 + warp * 16 + 2 * g;
#pragma unroll 1
        for (int j = 0; j < 16; j++) {
            if (j == PW_J) {
                st2(p, 0u, 0u);
                st2(p + 1024, 0u, 0u);
                if (t < 2) {
#pragma unroll
                    for (int e = 0; e < 4; e++) {
                        st2(scr + G_A + dst_off + e * 1024, 0u, 0u);
                        st2(scr + G_B + dst_off + e * 1024, 0u, 0u);
                    }
                }
            }
            uint32_t pb[2][4];
            ldsm_x4_t(pb[0], paddr + j * 1024);
            ldsm_x4_t(pb[1], paddr + j * 1024 + 512);
            mbar_wait(bar_full + stage * 8, ph, flag);
            const uint32_t base = sbase + stage * STAGE_BYTES + kh2 * 8192 + offT;
            uint32_t a[4][4];
#pragma unroll
            for (int ks = 0; ks < 4; ks++) ldsm_x4_t(a[ks], base + ks * 2048);
            mma16816(acc0, a[0], pb[0][0], pb[0][1]);
            mma16816(acc1, a[1], pb[0][2], pb[0][3]);
            mma16816(acc0, a[2], pb[1][0], pb[1][1]);
            mma16816(acc1, a[3], pb[1][2], pb[1][3]);
            __syncwarp();
            if (lane == 0) mbar_arrive_cnt(bar_empty + stage * 8, 1);
            if (++stage == NSTAGE) { stage = 0; ph ^= 1u; }
            if (j == 14) bar_sync(BAR_F, 288);
        }
        const float2 f = *reinterpret_cast<const float2*>(sptr + SM_F + t * 8);
        st2(p, enc((acc0[0] + acc1[0]) * f.x, tag), enc((acc0[2] + acc1[2]) * f.x, tag));
        st2(p + 1024, enc((acc0[1] + acc1[1]) * f.y, tag), enc((acc0[3] + acc1[3]) * f.y, tag));
        bar_arrive(BAR_O, 384);
    }
    PROFW(0, 7);
    const uint32_t offW0 = (warp >> 1) * 2048 + rowT + ((((uint32_t)(4 * (warp & 1) + ((lane >> 3) & 1))) ^ l8) << 4);
    const uint32_t offW1 = (warp >> 1) * 2048 + rowT + ((((uint32_t)(4 * (warp & 1) + 2 + ((lane >> 3) & 1))) ^ l8) << 4);
    {
        bar_sync(BAR_HS, 288);
        PROFW(0, 8);
        float acc0[4] = {0.f, 0.f, 0.f, 0.f}, acc1[4] = {0.f, 0.f, 0.f, 0.f};
        const uint32_t baddr = sbase + SM_HS + (g & 3) * HS_STRIDE + t * 4;
#pragma unroll 1
        for (int j = 0; j < 3; j++) {
            uint32_t b[4] = {0u, 0u, 0u, 0u};
            if (bvalid) {
#pragma unroll
                for (int e = 0; e < 4; e++) b[e] = lds32(baddr + j * 64 + e * 16);
            }
            mbar_wait(bar_full + stage * 8, ph, flag);
            const uint32_t base = sbase + stage * STAGE_BYTES;
            uint32_t a[4][4];
            ldsm_x4_t(a[0], base + offW0);
            ldsm_x4_t(a[1], base + offW1);
            ldsm_x4_t(a[2], base + 8192 + offW0);
            ldsm_x4_t(a[3], base + 8192 + offW1);
            mma16816(acc0, a[0], b[0], b[1]);
            mma16816(acc1, a[1], b[0], b[1]);
            mma16816(acc0, a[2], b[2], b[3]);
            mma16816(acc1, a[3], b[2], b[3]);
            ++stage;
        }
        {
            uint32_t b0 = 0u, b1_ = 0u;
            if (bvalid) { b0 = lds32(baddr + 192); b1_ = lds32(baddr + 208); }
            mbar_wait(bar_full + stage * 8, ph, flag);
            const uint32_t base = sbase + stage * STAGE_BYTES;
            uint32_t a[2][4];
            ldsm_x4_t(a[0], base + offW0);
            ldsm_x4_t(a[1], base + offW1);
            mma16816(acc0, a[0], b0, b1_);
            mma16816(acc1, a[1], b0, b1_);
            ++stage;
        }
        if (t < 2) {
            unsigned int* p = scr + G_B + dst_off;
            st2(p, enc(acc0[0], tag), enc(acc0[1], tag));
            st2(p + 1024, enc(acc0[2], tag), enc(acc0[3], tag));
            st2(p + 2048, enc(acc1[0], tag), enc(acc1[1], tag));
            st2(p + 3072, enc(acc1[2], tag), enc(acc1[3], tag));
        }
        bar_arrive(BAR_B, 288);
    }
    PROFW(0, 9);
    {
        bar_sync(BAR_OS, 384);
        PROFW(0, 10);
        float acc0[4] = {0.f, 0.f, 0.f, 0.f}, acc1[4] = {0.f, 0.f, 0.f, 0.f};
        const uint32_t baddr = sbase + SM_OS + (g & 3) * FR_STRIDE + t * 8;
#pragma unroll 1
        for (int j = 0; j < 4; j++) {
            uint2 b0 = make_uint2(0u, 0u), b1_ = make_uint2(0u, 0u);
            if (bvalid) { b0 = lds64(baddr + j * 64); b1_ = lds64(baddr + j * 64 + 32); }
            mbar_wait(bar_full + stage * 8, ph, flag);
            const uint32_t base = sbase + stage * STAGE_BYTES;
            uint32_t a[4][4];
            ldsm_x4_t(a[0], base + offW0);
            ldsm_x4_t(a[1], base + offW1);
            ldsm_x4_t(a[2], base + 8192 + offW0);
            ldsm_x4_t(a[3], base + 8192 + offW1);
            mma16816(acc0, a[0], b0.x, b0.y);
            mma16816(acc1, a[1], b0.x, b0.y);
            mma16816(acc0, a[2], b1_.x, b1_.y);
            mma16816(acc1, a[3], b1_.x, b1_.y);
            ++stage;
        }
        if (t < 2) {
            unsigned int* p = scr + G_A + dst_off;
            st2(p, enc(acc0[0], tag), enc(acc0[1], tag));
            st2(p + 1024, enc(acc0[2], tag), enc(acc0[3], tag));
            st2(p + 2048, enc(acc1[0], tag), enc(acc1[1], tag));
            st2(p + 3072, enc(acc1[2], tag), enc(acc1[3], tag));
        }
        bar_arrive(BAR_A, 288);
    }
    PROFW(0, 11);
}

typedef CUresult (*EncodeFn)(CUtensorMap*, CUtensorMapDataType, cuuint32_t, void*, const cuuint64_t*, const cuuint64_t*,
                             const cuuint32_t*, const cuuint32_t*, CUtensorMapInterleave, CUtensorMapSwizzle,
                             CUtensorMapL2promotion, CUtensorMapFloatOOBfill);

void make_2d(EncodeFn enc_fn, CUtensorMap* tm, void* base, uint64_t cols, uint64_t rows, uint32_t box_rows) {
    cuuint64_t gd[2] = {cols, rows};
    cuuint64_t gs[1] = {cols * 2};
    cuuint32_t bd[2] = {64, box_rows};
    cuuint32_t es[2] = {1, 1};
    enc_fn(tm, CU_TENSOR_MAP_DATA_TYPE_BFLOAT16, 2, base, gd, gs, bd, es, CU_TENSOR_MAP_INTERLEAVE_NONE,
           CU_TENSOR_MAP_SWIZZLE_128B, CU_TENSOR_MAP_L2_PROMOTION_L2_128B, CU_TENSOR_MAP_FLOAT_OOB_FILL_NONE);
}
void make_3d(EncodeFn enc_fn, CUtensorMap* tm, void* base, uint64_t cols, uint64_t rows, uint32_t box_rows, uint32_t box_blocks) {
    cuuint64_t gd[3] = {64, rows, cols / 64};
    cuuint64_t gs[2] = {cols * 2, 128};
    cuuint32_t bd[3] = {64, box_rows, box_blocks};
    cuuint32_t es[3] = {1, 1, 1};
    enc_fn(tm, CU_TENSOR_MAP_DATA_TYPE_BFLOAT16, 3, base, gd, gs, bd, es, CU_TENSOR_MAP_INTERLEAVE_NONE,
           CU_TENSOR_MAP_SWIZZLE_128B, CU_TENSOR_MAP_L2_PROMOTION_L2_128B, CU_TENSOR_MAP_FLOAT_OOB_FILL_NONE);
}

}

extern "C" void kernel_launch(void* const* d_in, const int* in_sizes, int n_in, void* d_out, int out_size) {
    (void)in_sizes; (void)n_in; (void)out_size;
    static TMaps maps;
    static void* cached[6] = {nullptr, nullptr, nullptr, nullptr, nullptr, nullptr};
    static EncodeFn enc_fn = nullptr;
    static void* scr = nullptr;
    if (!enc_fn) {
        cudaGetSymbolAddress(&scr, g_scratch);
        void* fn = nullptr;
        cudaDriverEntryPointQueryResult qr;
        cudaGetDriverEntryPoint("cuTensorMapEncodeTiled", &fn, cudaEnableDefault, &qr);
        enc_fn = (EncodeFn)fn;
        cudaFuncSetAttribute(fused_kernel, cudaFuncAttributeMaxDynamicSharedMemorySize, SM_ALLOC);
    }
    void* cur[6] = {d_in[3], d_in[6], d_in[1], d_in[2], d_in[8], d_in[4]};
    bool same = true;
    for (int i = 0; i < 6; i++) same = same && (cur[i] == cached[i]);
    if (!same) {
        make_2d(enc_fn, &maps.wq, d_in[3], 4096, 1024, 128);
        make_2d(enc_fn, &maps.w1, d_in[6], F_DIM, 1024, 128);
        make_3d(enc_fn, &maps.k, d_in[1], 128, 16 * SK, 64, 2);
        make_3d(enc_fn, &maps.v, d_in[2], 128, 16 * SK, 64, 2);
        make_3d(enc_fn, &maps.w2, d_in[8], 1024, F_DIM, 16, 4);
        make_3d(enc_fn, &maps.wo, d_in[4], 1024, 4096, 16, 4);
        for (int i = 0; i < 6; i++) cached[i] = cur[i];
    }
    fused_kernel<<<NCTA, NTHREADS, SM_ALLOC, cudaStreamPerThread>>>(
        (const __nv_bfloat16*)d_in[3], (const __nv_bfloat16*)d_in[0], (unsigned int*)scr, (__nv_bfloat16*)d_out,
        (const __nv_bfloat16*)d_in[10], (const __nv_bfloat16*)d_in[7], maps, (const __nv_bfloat16*)d_in[9]);
}
```

```cpp
#include <cuda_runtime.h>
#include <cuda.h>
#include <cuda_bf16.h>
#include <stdint.h>

namespace {

constexpr int NCTA = 128;
constexpr int NTHREADS = 416;
constexpr int NSTAGE = 12;
constexpr int STAGE_BYTES = 16384;

constexpr int D_MODEL = 1024;
constexpr int F_DIM = 3584;
constexpr int SK = 8192;

constexpr int SM_P = NSTAGE * STAGE_BYTES;
constexpr int SM_XS = SM_P;
constexpr int SM_YS = SM_P + 16384;
constexpr int SM_QS = SM_YS + 4160;
constexpr int SM_OS = SM_QS + 2304;
constexpr int SM_HS = SM_OS + 1152;
constexpr int SM_RED = SM_HS + 960;
constexpr int SM_MX = SM_RED + 2048;
constexpr int SM_LS = SM_MX + 256;
constexpr int SM_F = SM_LS + 256;
constexpr int SM_BAR = SM_F + 32;
constexpr int SM_FLAG = SM_BAR + 2 * NSTAGE * 8;
constexpr int SM_TOTAL = SM_FLAG + 8;
constexpr int SM_ALLOC = SM_TOTAL + 1024;

constexpr int XS_STRIDE = 1032 * 2;
constexpr int YS_STRIDE = 520 * 2;
constexpr int HS_STRIDE = 240;
constexpr int FR_STRIDE = 288;

#define PACE_T 652
#define PACE_LEAD 2
#define PACE_OFF PACE_T
#define PW_J 6
#define PACE_CAP 4
#define FP_GAP 160
#define OG_DELAY 400

constexpr int BAR_INIT = 0;
constexpr int BAR_CONS = 1;
constexpr int BAR_PAIR = 2;
constexpr int BAR_X = 6;
constexpr int BAR_ML = 7;
constexpr int BAR_O = 8;
constexpr int BAR_OS = 9;
constexpr int BAR_W1 = 10;
constexpr int BAR_HS = 11;
constexpr int BAR_A = 12;
constexpr int BAR_B = 13;
constexpr int BAR_F = 14;

struct TMaps {
    CUtensorMap wq, w1, k, v, w2, wo;
};

constexpr int G_EPOCH = 0;
constexpr int G_Q = G_EPOCH + NCTA * 4;
constexpr int G_H = G_Q + 2 * 4 * 4096;
constexpr int G_ML = G_H + 2 * F_DIM * 4;
constexpr int G_O = G_ML + NCTA * 16;
constexpr int G_A = G_O + NCTA * 1024;
constexpr int G_B = G_A + NCTA * 1024;
constexpr int G_TOTAL = G_B + NCTA * 1024;
__device__ __align__(1024) unsigned int g_scratch[G_TOTAL];

#define PROF(i)
#define PROFW(w, i)
__device__ __forceinline__ uint32_t smem_u32(const void* p) { return (uint32_t)__cvta_generic_to_shared(p); }
__device__ __forceinline__ uint32_t gtime32() { uint32_t t; asm volatile("mov.u32 %0, %globaltimer_lo;" : "=r"(t)); return t; }

__device__ __forceinline__ void mbar_init(uint32_t bar, uint32_t cnt) {
    asm volatile("mbarrier.init.shared::cta.b64 [%0], %1;" ::"r"(bar), "r"(cnt) : "memory");
}
__device__ __forceinline__ void mbar_expect_tx(uint32_t bar, uint32_t bytes) {
    asm volatile("mbarrier.arrive.expect_tx.shared::cta.b64 _, [%0], %1;" ::"r"(bar), "r"(bytes) : "memory");
}
__device__ __forceinline__ void mbar_arrive_cnt(uint32_t bar, uint32_t cnt) {
    asm volatile("mbarrier.arrive.shared::cta.b64 _, [%0], %1;" ::"r"(bar), "r"(cnt) : "memory");
}
__device__ __forceinline__ bool mbar_try(uint32_t bar, uint32_t parity) {
    uint32_t ok;
    asm volatile(
        "{\n.reg .pred p;\n"
        "mbarrier.try_wait.parity.shared::cta.b64 p, [%1], %2;\n"
        "selp.u32 %0, 1, 0, p;\n}\n"
        : "=r"(ok)
        : "r"(bar), "r"(parity)
        : "memory");
    return ok != 0;
}
__device__ __noinline__ void mbar_wait_slow(uint32_t bar, uint32_t parity, volatile uint32_t* flag) {
    long long t0 = clock64();
    for (uint32_t it = 0; it < 0x40000000u; it++) {
        if (mbar_try(bar, parity)) return;
        if ((it & 63u) == 63u) {
            if (*flag) return;
            if (clock64() - t0 > 2000000000LL) { *flag = 1u; return; }
        }
    }
}
__device__ __forceinline__ void mbar_wait(uint32_t bar, uint32_t parity, volatile uint32_t* flag) {
    if (mbar_try(bar, parity)) return;
    if (mbar_try(bar, parity)) return;
    mbar_wait_slow(bar, parity, flag);
}

__device__ __forceinline__ void tma_2d(uint32_t dst, const CUtensorMap* tm, int c0, int c1, uint32_t bar) {
    asm volatile(
        "cp.async.bulk.tensor.2d.shared::cluster.global.mbarrier::complete_tx::bytes.L2::cache_hint [%0], [%1, {%3, %4}], [%2], %5;"
        ::"r"(dst), "l"(tm), "r"(bar), "r"(c0), "r"(c1), "l"(0x12F0000000000000ull)
        : "memory");
}
__device__ __forceinline__ void tma_3d(uint32_t dst, const CUtensorMap* tm, int c0, int c1, int c2, uint32_t bar) {
    asm volatile(
        "cp.async.bulk.tensor.3d.shared::cluster.global.mbarrier::complete_tx::bytes.L2::cache_hint [%0], [%1, {%3, %4, %5}], [%2], %6;"
        ::"r"(dst), "l"(tm), "r"(bar), "r"(c0), "r"(c1), "r"(c2), "l"(0x12F0000000000000ull)
        : "memory");
}
__device__ __forceinline__ void bulk_load(uint32_t dst, const void* src, uint32_t bytes, uint32_t bar) {
    asm volatile("cp.async.bulk.shared::cluster.global.mbarrier::complete_tx::bytes [%0], [%1], %2, [%3];"
                 ::"r"(dst), "l"(src), "r"(bytes), "r"(bar)
                 : "memory");
}
__device__ __forceinline__ void prefetch_tmap(const CUtensorMap* tm) {
    asm volatile("prefetch.tensormap [%0];" ::"l"(tm) : "memory");
}
__device__ __forceinline__ void bar_sync(int id, int cnt) { asm volatile("bar.sync %0, %1;" ::"r"(id), "r"(cnt) : "memory"); }
__device__ __forceinline__ void bar_arrive(int id, int cnt) { asm volatile("bar.arrive %0, %1;" ::"r"(id), "r"(cnt) : "memory"); }

__device__ __forceinline__ void ldsm_x4(uint32_t (&r)[4], uint32_t addr) {
    asm volatile("ldmatrix.sync.aligned.m8n8.x4.shared.b16 {%0,%1,%2,%3}, [%4];"
                 : "=r"(r[0]), "=r"(r[1]), "=r"(r[2]), "=r"(r[3])
                 : "r"(addr)
                 : "memory");
}
__device__ __forceinline__ void ldsm_x4_t(uint32_t (&r)[4], uint32_t addr) {
    asm volatile("ldmatrix.sync.aligned.m8n8.x4.trans.shared.b16 {%0,%1,%2,%3}, [%4];"
                 : "=r"(r[0]), "=r"(r[1]), "=r"(r[2]), "=r"(r[3])
                 : "r"(addr)
                 : "memory");
}
__device__ __forceinline__ void mma16816(float (&c)[4], const uint32_t (&a)[4], uint32_t b0, uint32_t b1) {
    asm volatile(
        "mma.sync.aligned.m16n8k16.row.col.f32.bf16.bf16.f32 {%0,%1,%2,%3}, {%4,%5,%6,%7}, {%8,%9}, {%0,%1,%2,%3};"
        : "+f"(c[0]), "+f"(c[1]), "+f"(c[2]), "+f"(c[3])
        : "r"(a[0]), "r"(a[1]), "r"(a[2]), "r"(a[3]), "r"(b0), "r"(b1));
}
__device__ __forceinline__ uint32_t lds32(uint32_t addr) {
    uint32_t v;
    asm volatile("ld.shared.b32 %0, [%1];" : "=r"(v) : "r"(addr) : "memory");
    return v;
}
__device__ __forceinline__ uint2 lds64(uint32_t addr) {
    uint2 v;
    asm volatile("ld.shared.v2.b32 {%0, %1}, [%2];" : "=r"(v.x), "=r"(v.y) : "r"(addr) : "memory");
    return v;
}
__device__ __forceinline__ void sts32(uint32_t addr, uint32_t v) {
    asm volatile("st.shared.b32 [%0], %1;" ::"r"(addr), "r"(v) : "memory");
}
__device__ __forceinline__ void sts64(uint32_t addr, uint32_t a, uint32_t b) {
    asm volatile("st.shared.v2.b32 [%0], {%1, %2};" ::"r"(addr), "r"(a), "r"(b) : "memory");
}

__device__ __forceinline__ float bf16r(float x) { return __bfloat162float(__float2bfloat16_rn(x)); }
__device__ __forceinline__ uint32_t pack_bf16(float lo, float hi) {
    __nv_bfloat162 v = __floats2bfloat162_rn(lo, hi);
    return *reinterpret_cast<uint32_t*>(&v);
}
__device__ __forceinline__ float bf_lo(uint32_t u) { return __uint_as_float(u << 16); }
__device__ __forceinline__ float bf_hi(uint32_t u) { return __uint_as_float(u & 0xffff0000u); }

__device__ __forceinline__ uint32_t enc(float v, uint32_t tag) { return (__float_as_uint(v) & ~3u) | tag; }
__device__ __forceinline__ float dec(uint32_t u) { return __uint_as_float(u & ~3u); }
__device__ __forceinline__ void st2(unsigned int* p, uint32_t a, uint32_t b) {
    asm volatile("st.relaxed.gpu.global.v2.b32 [%0], {%1, %2};" ::"l"(p), "r"(a), "r"(b) : "memory");
}
__device__ __forceinline__ void st4(unsigned int* p, uint32_t a, uint32_t b, uint32_t c, uint32_t d) {
    asm volatile("st.relaxed.gpu.global.v4.b32 [%0], {%1, %2, %3, %4};" ::"l"(p), "r"(a), "r"(b), "r"(c), "r"(d) : "memory");
}
__device__ __forceinline__ uint32_t ld1(const unsigned int* p) {
    uint32_t v;
    asm volatile("ld.relaxed.gpu.global.b32 %0, [%1];" : "=r"(v) : "l"(p) : "memory");
    return v;
}
__device__ __forceinline__ uint2 ld2(const unsigned int* p) {
    uint2 v;
    asm volatile("ld.relaxed.gpu.global.v2.b32 {%0, %1}, [%2];" : "=r"(v.x), "=r"(v.y) : "l"(p) : "memory");
    return v;
}
__device__ __forceinline__ uint4 ld4(const unsigned int* p) {
    uint4 v;
    asm volatile("ld.relaxed.gpu.global.v4.b32 {%0, %1, %2, %3}, [%4];" : "=r"(v.x), "=r"(v.y), "=r"(v.z), "=r"(v.w) : "l"(p) : "memory");
    return v;
}
__device__ __forceinline__ uint32_t bad4(const uint4& v, uint32_t tag) { return (v.x ^ tag) | (v.y ^ tag) | (v.z ^ tag) | (v.w ^ tag); }
__device__ __forceinline__ bool warp_ok(uint32_t bad) { return __all_sync(0xffffffffu, (bad & 3u) == 0u); }
__device__ __forceinline__ void spin_cycles(int n) {
    const uint32_t t0 = (uint32_t)clock64();
    for (int it = 0; it < 1000 && (int)((uint32_t)clock64() - t0) < n; it++) {}
}
constexpr uint32_t POLL_LIMIT = 1u << 21;

__device__ __forceinline__ void gemv_tile4(float (&acc0)[4], float (&acc1)[4], uint32_t a_addr, uint32_t b_addr, bool bvalid) {
    uint32_t a[4][4];
    uint32_t b[4][2];
#pragma unroll
    for (int ks = 0; ks < 4; ks++) ldsm_x4_t(a[ks], a_addr + ks * 2048);
#pragma unroll
    for (int ks = 0; ks < 4; ks++) {
        b[ks][0] = bvalid ? lds32(b_addr + ks * 32) : 0u;
        b[ks][1] = bvalid ? lds32(b_addr + ks * 32 + 16) : 0u;
    }
#pragma unroll
    for (int ks = 0; ks < 4; ks++) {
        if (ks & 1) mma16816(acc1, a[ks], b[ks][0], b[ks][1]);
        else mma16816(acc0, a[ks], b[ks][0], b[ks][1]);
    }
}

__device__ __forceinline__ float final_sum(const unsigned int* buf, int lane, uint32_t tag, bool backoff) {
    const unsigned int* p = buf + (lane >> 3) * 256 + (lane & 7) * 4;
    uint4 d[8];
    for (uint32_t it = 0; it < POLL_LIMIT; it++) {
        uint32_t bad = 0;
#pragma unroll
        for (int i = 0; i < 8; i++) { d[i] = ld4(p + i * 32); bad |= bad4(d[i], tag); }
        if (warp_ok(bad)) break;
        if (backoff) __nanosleep(100);
    }
    float s0 = 0.f, s1 = 0.f, s2 = 0.f, s3 = 0.f;
#pragma unroll
    for (int i = 0; i < 8; i++) { s0 += dec(d[i].x); s1 += dec(d[i].y); s2 += dec(d[i].z); s3 += dec(d[i].w); }
    const bool hi = lane & 16;
    float u0 = hi ? s0 : s2, u1 = hi ? s1 : s3;
    float k0 = hi ? s2 : s0, k1 = hi ? s3 : s1;
    k0 += __shfl_xor_sync(0xffffffffu, u0, 16);
    k1 += __shfl_xor_sync(0xffffffffu, u1, 16);
    const bool od = lane & 8;
    const float w = od ? k0 : k1;
    float r = od ? k1 : k0;
    r += __shfl_xor_sync(0xffffffffu, w, 8);
    return r;
}

__global__ void __launch_bounds__(NTHREADS, 1)
fused_kernel(const __nv_bfloat16* __restrict__ wq, const __nv_bfloat16* __restrict__ x, unsigned int* __restrict__ scr,
             __nv_bfloat16* __restrict__ out, const __nv_bfloat16* __restrict__ gate_w, const __nv_bfloat16* __restrict__ b1,
             const __grid_constant__ TMaps maps, const __nv_bfloat16* __restrict__ b2) {
    extern __shared__ unsigned char smem_raw[];
    const uint32_t sbase = (smem_u32(smem_raw) + 1023u) & ~1023u;
    unsigned char* sptr = smem_raw + (sbase - smem_u32(smem_raw));
    volatile uint32_t* flag = reinterpret_cast<volatile uint32_t*>(sptr + SM_FLAG);

    const int c = blockIdx.x;
    const int tid = threadIdx.x;
    const int warp = tid >> 5;
    const int lane = tid & 31;
    const bool has_w1 = c < 112;
    const int kb = c >> 2, nb = c & 3;
    const uint32_t bar_full = sbase + SM_BAR;
    const uint32_t bar_empty = sbase + SM_BAR + NSTAGE * 8;

    PROFW(0, 0);
    if (warp == 8) {
        const int n_w1 = has_w1 ? 4 : 0;
        const int n_tiles = 44 + n_w1;
        const int kv_row0 = (c >> 3) * SK + (c & 7) * 1024;
        uint32_t due = 0;
        if (lane == 0) {
#pragma unroll
            for (int j = 0; j < PACE_LEAD; j++) mbar_init(bar_full + j * 8, 1);
            asm volatile("fence.mbarrier_init.release.cluster;" ::: "memory");
            asm volatile("fence.proxy.async.shared::cta;" ::: "memory");
#pragma unroll
            for (int j = 0; j < PACE_LEAD; j++) {
                mbar_expect_tx(bar_full + j * 8, STAGE_BYTES);
                tma_2d(sbase + j * STAGE_BYTES, &maps.wq, (c >> 1) * 64, (c & 1) * 512 + j * 128, bar_full + j * 8);
            }
            due = gtime32() + PACE_OFF + (c >> 1) * PACE_T / 64;
#pragma unroll
            for (int i = PACE_LEAD; i < NSTAGE; i++) mbar_init(bar_full + i * 8, 1);
#pragma unroll
            for (int i = 0; i < NSTAGE; i++) mbar_init(bar_empty + i * 8, 8);
            *flag = 0u;
            asm volatile("fence.mbarrier_init.release.cluster;" ::: "memory");
            asm volatile("fence.proxy.async.shared::cta;" ::: "memory");
            prefetch_tmap(&maps.w1);
            prefetch_tmap(&maps.k);
            prefetch_tmap(&maps.v);
            prefetch_tmap(&maps.w2);
            prefetch_tmap(&maps.wo);
        }
        __syncwarp();
        bar_arrive(BAR_INIT, NTHREADS);
        if (lane == 0) {
            int landed = 0;
            for (int i = PACE_LEAD; i < n_tiles; i++) {
                while (landed + PACE_CAP <= i) {
                    mbar_wait(bar_full + (landed % NSTAGE) * 8, (uint32_t)(landed / NSTAGE) & 1u, flag);
                    landed++;
                }
                const int stage = i % NSTAGE;
                if (i >= NSTAGE) mbar_wait(bar_empty + stage * 8, (uint32_t)(i / NSTAGE - 1) & 1u, flag);
                for (int it = 0; it < 100000 && (int)(gtime32() - due) < 0; it++) {}
                const uint32_t dst = sbase + stage * STAGE_BYTES;
                const uint32_t fb = bar_full + stage * 8;
                int j = i - 4;
                if (j < 0) {
                    mbar_expect_tx(fb, STAGE_BYTES);
                    tma_2d(dst, &maps.wq, (c >> 1) * 64, (c & 1) * 512 + i * 128, fb);
                    due += (j == -1 && !has_w1) ? PACE_T * 9 / 2 : PACE_T;
                } else if (j < n_w1) {
                    mbar_expect_tx(fb, STAGE_BYTES);
                    tma_2d(dst, &maps.w1, (c >> 1) * 64, (c & 1) * 512 + j * 128, fb);
                    due += PACE_T * 7 / 8;
                } else if (j < 32 + n_w1) {
                    j -= n_w1;
                    mbar_expect_tx(fb, STAGE_BYTES);
                    tma_3d(dst, j < 16 ? &maps.k : &maps.v, 0, kv_row0 + (j & 15) * 64, 0, fb);
                    due += PACE_T;
                } else {
                    j -= 32 + n_w1;
                    const CUtensorMap* tm = j < 4 ? &maps.w2 : &maps.wo;
                    const int row = j < 4 ? kb * 112 + j * 32 : kb * 128 + (j - 4) * 32;
                    mbar_expect_tx(fb, j != 3 ? STAGE_BYTES : STAGE_BYTES / 2);
                    tma_3d(dst, tm, 0, row, nb * 4, fb);
                    if (j != 3) tma_3d(dst + 8192, tm, 0, row + 16, nb * 4, fb);
                    due += j != 3 ? PACE_T : PACE_T / 2;
                }
            }
            PROF(20);
        }
        return;
    }

    const int g = lane >> 2;
    const int t = lane & 3;
    const int khalf = c & 1;
    const int pair = c >> 3;
    const int mt = warp & 3;
    const int kh2 = warp >> 2;
    const uint32_t epoch = ld1(scr + G_EPOCH + c * 4) + 1u;
    unsigned int* const q_dst = scr + G_Q + (khalf * 4 + 2 * t) * 4096 + (c >> 1) * 64 + mt * 16 + 2 * g;
    unsigned int* const h_dst = scr + G_H + (khalf * F_DIM + (c >> 1) * 64 + mt * 16 + g) * 4 + 2 * t;
    if (warp < 8) {
        asm volatile("prefetch.global.L2 [%0];" ::"l"(wq + (size_t)(khalf * 512 + tid) * 4096 + (c >> 1) * 64));
        const uint4 x0 = __ldg(reinterpret_cast<const uint4*>(x) + tid);
        const uint4 x1 = __ldg(reinterpret_cast<const uint4*>(x) + 256 + tid);
        if (warp < 4 && t < 2) {
            st2(q_dst, 0u, 0u);
            st2(q_dst + 4096, 0u, 0u);
            if (has_w1) {
                st2(h_dst, 0u, 0u);
                st2(h_dst + 32, 0u, 0u);
            }
        }
        *reinterpret_cast<uint4*>(sptr + SM_XS + (tid >> 7) * XS_STRIDE + (tid & 127) * 16) = x0;
        *reinterpret_cast<uint4*>(sptr + SM_XS + (2 + (tid >> 7)) * XS_STRIDE + (tid & 127) * 16) = x1;
    }
    const uint32_t tag = 1u + epoch % 3u;

    if (warp >= 9) {
        float gate = 0.f, b2v = 0.f;
        if (warp == 9) {
            uint4 gw[4];
#pragma unroll
            for (int i = 0; i < 4; i++) gw[i] = __ldg(reinterpret_cast<const uint4*>(gate_w) + i * 32 + lane);
            b2v = __bfloat162float(b2[c * 8 + (lane & 7)]);
            bar_sync(BAR_INIT, NTHREADS);
            float zz = 0.f;
#pragma unroll 1
            for (int b = 0; b < 4; b++) {
                float zs = 0.f;
#pragma unroll
                for (int i = 0; i < 4; i++) {
                    const uint4 xv = *reinterpret_cast<const uint4*>(sptr + SM_XS + b * XS_STRIDE + (i * 32 + lane) * 16);
                    const uint32_t xa[4] = {xv.x, xv.y, xv.z, xv.w};
                    const uint32_t wa[4] = {gw[i].x, gw[i].y, gw[i].z, gw[i].w};
#pragma unroll
                    for (int e = 0; e < 4; e++) {
                        zs += bf16r(bf_lo(xa[e]) * bf_lo(wa[e]));
                        zs += bf16r(bf_hi(xa[e]) * bf_hi(wa[e]));
                    }
                }
#pragma unroll
                for (int o = 16; o > 0; o >>= 1) zs += __shfl_xor_sync(0xffffffffu, zs, o);
                if ((lane >> 3) == b) zz = zs;
            }
            bar_arrive(BAR_X, 288);
            zz = bf16r(zz);
            gate = bf16r(1.0f / (1.0f + __expf(-zz)));
            if (lane == 0) *reinterpret_cast<volatile unsigned int*>(scr + G_EPOCH + c * 4) = epoch;
            PROF(12);
        } else if (warp == 11) {
            const bool has4 = lane < 16;
            float bias[4];
#pragma unroll
            for (int i = 0; i < 4; i++) bias[i] = (i < 3 || has4) ? __bfloat162float(b1[kb * 112 + i * 32 + lane]) : 0.f;
            bar_sync(BAR_INIT, NTHREADS);
            bar_sync(BAR_W1, 288);
            const unsigned int* p = scr + G_H + (kb * 112 + lane) * 4;
            uint4 d[4][2];
            for (uint32_t it = 0; it < POLL_LIMIT; it++) {
                __nanosleep(1000);
                uint32_t bad = 0;
#pragma unroll
                for (int i = 0; i < 4; i++) {
                    if (i < 3 || has4) {
                        d[i][0] = ld4(p + i * 128);
                        d[i][1] = ld4(p + i * 128 + F_DIM * 4);
                        bad |= bad4(d[i][0], tag) | bad4(d[i][1], tag);
                    }
                }
                if (warp_ok(bad)) break;
            }
            PROF(16);
#pragma unroll
            for (int i = 0; i < 4; i++) {
                if (i < 3 || has4) {
                    const int cl = i * 32 + lane;
                    const uint32_t u0[4] = {d[i][0].x, d[i][0].y, d[i][0].z, d[i][0].w};
                    const uint32_t u1[4] = {d[i][1].x, d[i][1].y, d[i][1].z, d[i][1].w};
#pragma unroll
                    for (int b = 0; b < 4; b++) {
                        float v = bf16r(dec(u0[b]) + dec(u1[b]));
                        v = bf16r(v + bias[i]);
                        const float inner = 0.7978845608028654f * (v + 0.044715f * v * v * v);
                        const float hv = 0.5f * v * (1.0f + tanhf(inner));
                        *reinterpret_cast<__nv_bfloat16*>(sptr + SM_HS + b * HS_STRIDE + cl * 2) = __float2bfloat16_rn(hv);
                    }
                }
            }
            bar_arrive(BAR_HS, 288);
            PROF(18);
        } else if (warp == 12) {
            bar_sync(BAR_INIT, NTHREADS);
            bar_sync(BAR_ML, 64);
            const unsigned int* p = scr + G_ML + pair * 128 + lane * 4;
            uint4 d;
            for (uint32_t it = 0; it < POLL_LIMIT; it++) {
                __nanosleep(1000);
                d = ld4(p);
                if (warp_ok(bad4(d, tag))) break;
            }
            const float m0 = dec(d.x), m1 = dec(d.z);
            float M0 = m0, M1 = m1;
#pragma unroll
            for (int o = 4; o < 32; o <<= 1) {
                M0 = fmaxf(M0, __shfl_xor_sync(0xffffffffu, M0, o));
                M1 = fmaxf(M1, __shfl_xor_sync(0xffffffffu, M1, o));
            }
            const float w0 = exp2f((m0 - M0) * 1.4426950408889634f), w1 = exp2f((m1 - M1) * 1.4426950408889634f);
            float L0 = w0 * dec(d.y), L1 = w1 * dec(d.w);
#pragma unroll
            for (int o = 4; o < 32; o <<= 1) {
                L0 += __shfl_xor_sync(0xffffffffu, L0, o);
                L1 += __shfl_xor_sync(0xffffffffu, L1, o);
            }
            if (g == (c & 7)) *reinterpret_cast<float2*>(sptr + SM_F + t * 8) = make_float2(w0 / L0, w1 / L1);
            bar_arrive(BAR_F, 288);
            PROF(13);
        } else {
            bar_sync(BAR_INIT, NTHREADS);
        }
        {
            const int hb = warp - 9;
            const unsigned int* po = scr + G_O + ((hb * 4 + (kb >> 3)) * 8 + (kb & 7)) * 1024 + lane * 4;
            uint4 d[8];
            uint32_t pend = 0xffu;
            bar_sync(BAR_O, 384);
            __nanosleep(OG_DELAY);
            for (uint32_t it = 0; it < POLL_LIMIT; it++) {
#pragma unroll
                for (int s = 0; s < 8; s++)
                    if (pend & (1u << s)) d[s] = ld4(po + s * 128);
#pragma unroll
                for (int s = 0; s < 8; s++)
                    if ((pend & (1u << s)) && warp_ok(bad4(d[s], tag))) pend &= ~(1u << s);
                if (pend == 0u) break;
                __nanosleep(100);
            }
            float o0 = 0.f, o1 = 0.f, o2 = 0.f, o3 = 0.f;
#pragma unroll
            for (int s = 0; s < 8; s++) {
                o0 += dec(d[s].x);
                o1 += dec(d[s].y);
                o2 += dec(d[s].z);
                o3 += dec(d[s].w);
            }
            sts64(sbase + SM_OS + hb * FR_STRIDE + lane * 8, pack_bf16(o0, o2), pack_bf16(o1, o3));
            bar_arrive(BAR_OS, 384);
        }
        if (warp != 9) return;
        PROF(14);
        bar_sync(BAR_B, 288);
        const float bv = bf16r(bf16r(final_sum(scr + G_B + c * 1024, lane, tag, true)) + b2v);
        const float bterm = bf16r(bf16r(1.0f - gate) * bv);
        PROF(17);
        bar_sync(BAR_A, 288);
        const float aterm = bf16r(gate * bf16r(final_sum(scr + G_A + c * 1024, lane, tag, false)));
        out[(lane >> 3) * D_MODEL + c * 8 + (lane & 7)] = __float2bfloat16_rn(aterm + bterm);
        PROF(19);
        return;
    }

    bar_sync(BAR_INIT, NTHREADS);
    PROFW(0, 1);

    int stage = 0;
    uint32_t ph = 0;
    const uint32_t l8 = lane & 7;
    const uint32_t rowT = (l8 + 8 * (lane >> 4)) * 128;
    const uint32_t offT = rowT + ((((uint32_t)(2 * mt + ((lane >> 3) & 1))) ^ l8) << 4);
    const bool bvalid = g < 4;
    const int dst_off = ((nb * 32 + warp * 4) * 32 + kb) * 32 + g * 4 + 2 * t;

    {
        float acc0[4] = {0.f, 0.f, 0.f, 0.f}, acc1[4] = {0.f, 0.f, 0.f, 0.f};
        const uint32_t baddr = sbase + SM_XS + (g & 3) * XS_STRIDE + (khalf * 512 + kh2 * 64 + 2 * t) * 2;
#pragma unroll 1
        for (int j = 0; j < 4; j++) {
            mbar_wait(bar_full + stage * 8, ph, flag);
            gemv_tile4(acc0, acc1, sbase + stage * STAGE_BYTES + kh2 * 8192 + offT, baddr + j * 256, bvalid);
            __syncwarp();
            if (lane == 0) mbar_arrive_cnt(bar_empty + stage * 8, 1);
            ++stage;
        }
        float4* red = reinterpret_cast<float4*>(sptr + SM_RED) + mt * 16 + (g * 2 + (t & 1));
        if (kh2 == 1 && t < 2) *red = make_float4(acc0[0] + acc1[0], acc0[1] + acc1[1], acc0[2] + acc1[2], acc0[3] + acc1[3]);
        bar_sync(BAR_PAIR + mt, 64);
        if (kh2 == 0 && t < 2) {
            const float4 o = *red;
            st2(q_dst, enc(acc0[0] + acc1[0] + o.x, tag), enc(acc0[2] + acc1[2] + o.z, tag));
            st2(q_dst + 4096, enc(acc0[1] + acc1[1] + o.y, tag), enc(acc0[3] + acc1[3] + o.w, tag));
        }
    }
    PROFW(0, 2);
    if (has_w1) {
        {
            uint4 xv[4];
#pragma unroll
            for (int i = 0; i < 4; i++) xv[i] = *reinterpret_cast<const uint4*>(sptr + SM_XS + mt * XS_STRIDE + (i * 32 + lane) * 16);
            const uint4 xs = *reinterpret_cast<const uint4*>(sptr + SM_XS + mt * XS_STRIDE + (khalf * 64 + kh2 * 32 + lane) * 16);
            float s0 = 0.f, s1 = 0.f;
#pragma unroll
            for (int i = 0; i < 4; i++) {
                const uint32_t xa[4] = {xv[i].x, xv[i].y, xv[i].z, xv[i].w};
#pragma unroll
                for (int e = 0; e < 4; e++) { s0 += bf_lo(xa[e]); s1 += bf_hi(xa[e]); }
            }
            float s = s0 + s1;
#pragma unroll
            for (int o = 16; o > 0; o >>= 1) s += __shfl_xor_sync(0xffffffffu, s, o);
            const float mean = s * (1.0f / 1024.0f);
            float q0 = 0.f, q1 = 0.f;
#pragma unroll
            for (int i = 0; i < 4; i++) {
                const uint32_t xa[4] = {xv[i].x, xv[i].y, xv[i].z, xv[i].w};
#pragma unroll
                for (int e = 0; e < 4; e++) {
                    const float d0 = bf_lo(xa[e]) - mean, d1 = bf_hi(xa[e]) - mean;
                    q0 = fmaf(d0, d0, q0);
                    q1 = fmaf(d1, d1, q1);
                }
            }
            float q = q0 + q1;
#pragma unroll
            for (int o = 16; o > 0; o >>= 1) q += __shfl_xor_sync(0xffffffffu, q, o);
            const float mb = bf16r(mean);
            const float vb = bf16r(q * (1.0f / 1024.0f));
            const float den = bf16r(sqrtf(bf16r(vb + 1e-5f)));
            const uint32_t xa[4] = {xs.x, xs.y, xs.z, xs.w};
            uint32_t ya[4];
#pragma unroll
            for (int e = 0; e < 4; e++) ya[e] = pack_bf16(bf16r(bf_lo(xa[e]) - mb) / den, bf16r(bf_hi(xa[e]) - mb) / den);
            *reinterpret_cast<uint4*>(sptr + SM_YS + mt * YS_STRIDE + (kh2 * 32 + lane) * 16) = make_uint4(ya[0], ya[1], ya[2], ya[3]);
            bar_sync(BAR_CONS, 256);
        }
        float acc0[4] = {0.f, 0.f, 0.f, 0.f}, acc1[4] = {0.f, 0.f, 0.f, 0.f};
        const uint32_t baddr = sbase + SM_YS + (g & 3) * YS_STRIDE + (kh2 * 64 + 2 * t) * 2;
#pragma unroll 1
        for (int j = 0; j < 4; j++) {
            mbar_wait(bar_full + stage * 8, ph, flag);
            gemv_tile4(acc0, acc1, sbase + stage * STAGE_BYTES + kh2 * 8192 + offT, baddr + j * 256, bvalid);
            __syncwarp();
            if (lane == 0) mbar_arrive_cnt(bar_empty + stage * 8, 1);
            ++stage;
        }
        float4* red = reinterpret_cast<float4*>(sptr + SM_RED + 1024) + mt * 16 + (g * 2 + (t & 1));
        if (kh2 == 1 && t < 2) *red = make_float4(acc0[0] + acc1[0], acc0[1] + acc1[1], acc0[2] + acc1[2], acc0[3] + acc1[3]);
        bar_sync(BAR_PAIR + mt, 64);
        if (kh2 == 0 && t < 2) {
            const float4 o = *red;
            st2(h_dst, enc(acc0[0] + acc1[0] + o.x, tag), enc(acc0[1] + acc1[1] + o.y, tag));
            st2(h_dst + 32, enc(acc0[2] + acc1[2] + o.z, tag), enc(acc0[3] + acc1[3] + o.w, tag));
        }
    } else {
        mbar_wait(bar_full + stage * 8, ph, flag);
    }
    bar_arrive(BAR_W1, 288);
    PROFW(0, 3);
    uint32_t qf[8][2];
    {
        const unsigned int* p = scr + G_Q + (pair >> 2) * 4096 + (pair & 3) * 1024 + tid * 4;
        uint4 d0, d1;
        for (uint32_t it = 0; it < POLL_LIMIT; it++) {
            d0 = ld4(p);
            d1 = ld4(p + 4 * 4096);
            if (warp_ok(bad4(d0, tag) | bad4(d1, tag))) break;
            __nanosleep(200);
        }
        sts64(sbase + SM_QS + warp * FR_STRIDE + lane * 8,
              pack_bf16(dec(d0.x) + dec(d1.x), dec(d0.z) + dec(d1.z)), pack_bf16(dec(d0.y) + dec(d1.y), dec(d0.w) + dec(d1.w)));
        bar_sync(BAR_CONS, 256);
#pragma unroll
        for (int ks = 0; ks < 8; ks++) {
            const uint2 v = lds64(sbase + SM_QS + g * FR_STRIDE + (ks * 4 + t) * 8);
            qf[ks][0] = v.x;
            qf[ks][1] = v.y;
        }
    }
    PROFW(0, 4);
    float sc[8][4];
    {
        int st = stage + kh2;
        uint32_t php = ph;
        const uint32_t krow = mt * 16 + l8 + 8 * ((lane >> 3) & 1);
        const uint32_t khi = lane >> 4;
#pragma unroll
        for (int i = 0; i < 8; i++) {
            mbar_wait(bar_full + st * 8, php, flag);
            const uint32_t base = sbase + st * STAGE_BYTES + krow * 128;
            float c0[4] = {0.f, 0.f, 0.f, 0.f}, c1[4] = {0.f, 0.f, 0.f, 0.f};
            uint32_t a[8][4];
#pragma unroll
            for (int ks = 0; ks < 8; ks++)
                ldsm_x4(a[ks], base + (ks >> 2) * 8192 + (((uint32_t)((ks & 3) * 2) + khi) ^ l8) * 16);
#pragma unroll
            for (int ks = 0; ks < 8; ks++) {
                if (ks & 1) mma16816(c1, a[ks], qf[ks][0], qf[ks][1]);
                else mma16816(c0, a[ks], qf[ks][0], qf[ks][1]);
            }
            __syncwarp();
            if (lane == 0) mbar_arrive_cnt(bar_empty + st * 8, 2);
#pragma unroll
            for (int e = 0; e < 4; e++) sc[i][e] = bf16r(bf16r(c0[e] + c1[e]) * 0.08838834764831845f);
            st += 2;
            if (st >= NSTAGE) { st -= NSTAGE; php ^= 1u; }
        }
        stage += 16 - NSTAGE;
        ph ^= 1u;
        if (stage >= NSTAGE) { stage -= NSTAGE; ph ^= 1u; }
    }
    PROFW(0, 5);
    {
        float m0 = sc[0][0], m1 = sc[0][1];
#pragma unroll
        for (int i = 0; i < 8; i++) {
            m0 = fmaxf(m0, fmaxf(sc[i][0], sc[i][2]));
            m1 = fmaxf(m1, fmaxf(sc[i][1], sc[i][3]));
        }
#pragma unroll
        for (int o = 4; o < 32; o <<= 1) {
            m0 = fmaxf(m0, __shfl_xor_sync(0xffffffffu, m0, o));
            m1 = fmaxf(m1, __shfl_xor_sync(0xffffffffu, m1, o));
        }
        float2* mx = reinterpret_cast<float2*>(sptr + SM_MX);
        if (g == 0) mx[warp * 4 + t] = make_float2(m0, m1);
        bar_sync(BAR_X, 288);
#pragma unroll
        for (int w = 0; w < 8; w++) {
            const float2 v = mx[w * 4 + t];
            m0 = fmaxf(m0, v.x);
            m1 = fmaxf(m1, v.y);
        }
        float l0 = 0.f, l1 = 0.f;
#pragma unroll
        for (int i = 0; i < 8; i++) {
            const float e0 = exp2f((sc[i][0] - m0) * 1.4426950408889634f);
            const float e1 = exp2f((sc[i][1] - m1) * 1.4426950408889634f);
            const float e2 = exp2f((sc[i][2] - m0) * 1.4426950408889634f);
            const float e3 = exp2f((sc[i][3] - m1) * 1.4426950408889634f);
            l0 += e0 + e2;
            l1 += e1 + e3;
            const uint32_t key = (2 * i + kh2) * 64 + mt * 16 + g;
            sts32(sbase + SM_P + key * 16 + t * 4, pack_bf16(e0, e1));
            sts32(sbase + SM_P + (key + 8) * 16 + t * 4, pack_bf16(e2, e3));
        }
#pragma unroll
        for (int o = 4; o < 32; o <<= 1) {
            l0 += __shfl_xor_sync(0xffffffffu, l0, o);
            l1 += __shfl_xor_sync(0xffffffffu, l1, o);
        }
        float2* ls = reinterpret_cast<float2*>(sptr + SM_LS);
        if (g == 0) ls[warp * 4 + t] = make_float2(l0, l1);
        bar_sync(BAR_CONS, 256);
        if (warp == 0) {
            l0 = 0.f;
            l1 = 0.f;
#pragma unroll
            for (int w = 0; w < 8; w++) {
                const float2 v = ls[w * 4 + t];
                l0 += v.x;
                l1 += v.y;
            }
            if (g == 0) st4(scr + G_ML + c * 16 + t * 4, enc(m0, tag), enc(l0, tag), enc(m1, tag), enc(l1, tag));
            bar_arrive(BAR_ML, 64);
        }
    }
    PROFW(0, 6);
    {
        float acc0[4] = {0.f, 0.f, 0.f, 0.f}, acc1[4] = {0.f, 0.f, 0.f, 0.f};
        const uint32_t paddr = sbase + SM_P + lane * 16;
        unsigned int* p = scr + G_O + ((pair * 8 + 2 * t) * 8 + (c & 7)) * 128 + warp * 16 + 2 * g;
#pragma unroll 1
        for (int j = 0; j < 16; j++) {
            if (j == PW_J) {
                st2(p, 0u, 0u);
                st2(p + 1024, 0u, 0u);
                if (t < 2) {
#pragma unroll
                    for (int e = 0; e < 4; e++) {
                        st2(scr + G_A + dst_off + e * 1024, 0u, 0u);
                        st2(scr + G_B + dst_off + e * 1024, 0u, 0u);
                    }
                }
            }
            uint32_t pb[2][4];
            ldsm_x4_t(pb[0], paddr + j * 1024);
            ldsm_x4_t(pb[1], paddr + j * 1024 + 512);
            mbar_wait(bar_full + stage * 8, ph, flag);
            const uint32_t base = sbase + stage * STAGE_BYTES + kh2 * 8192 + offT;
            uint32_t a[4][4];
#pragma unroll
            for (int ks = 0; ks < 4; ks++) ldsm_x4_t(a[ks], base + ks * 2048);
            mma16816(acc0, a[0], pb[0][0], pb[0][1]);
            mma16816(acc1, a[1], pb[0][2], pb[0][3]);
            mma16816(acc0, a[2], pb[1][0], pb[1][1]);
            mma16816(acc1, a[3], pb[1][2], pb[1][3]);
            __syncwarp();
            if (lane == 0) mbar_arrive_cnt(bar_empty + stage * 8, 1);
            if (++stage == NSTAGE) { stage = 0; ph ^= 1u; }
            if (j == 14) bar_sync(BAR_F, 288);
        }
        const float2 f = *reinterpret_cast<const float2*>(sptr + SM_F + t * 8);
        st2(p, enc((acc0[0] + acc1[0]) * f.x, tag), enc((acc0[2] + acc1[2]) * f.x, tag));
        st2(p + 1024, enc((acc0[1] + acc1[1]) * f.y, tag), enc((acc0[3] + acc1[3]) * f.y, tag));
        bar_arrive(BAR_O, 384);
    }
    PROFW(0, 7);
    const uint32_t offW0 = (warp >> 1) * 2048 + rowT + ((((uint32_t)(4 * (warp & 1) + ((lane >> 3) & 1))) ^ l8) << 4);
    const uint32_t offW1 = (warp >> 1) * 2048 + rowT + ((((uint32_t)(4 * (warp & 1) + 2 + ((lane >> 3) & 1))) ^ l8) << 4);
    {
        bar_sync(BAR_HS, 288);
        PROFW(0, 8);
        float acc0[4] = {0.f, 0.f, 0.f, 0.f}, acc1[4] = {0.f, 0.f, 0.f, 0.f};
        const uint32_t baddr = sbase + SM_HS + (g & 3) * HS_STRIDE + t * 4;
#pragma unroll 1
        for (int j = 0; j < 3; j++) {
            uint32_t b[4] = {0u, 0u, 0u, 0u};
            if (bvalid) {
#pragma unroll
                for (int e = 0; e < 4; e++) b[e] = lds32(baddr + j * 64 + e * 16);
            }
            mbar_wait(bar_full + stage * 8, ph, flag);
            const uint32_t base = sbase + stage * STAGE_BYTES;
            uint32_t a[4][4];
            ldsm_x4_t(a[0], base + offW0);
            ldsm_x4_t(a[1], base + offW1);
            ldsm_x4_t(a[2], base + 8192 + offW0);
            ldsm_x4_t(a[3], base + 8192 + offW1);
            mma16816(acc0, a[0], b[0], b[1]);
            mma16816(acc1, a[1], b[0], b[1]);
            mma16816(acc0, a[2], b[2], b[3]);
            mma16816(acc1, a[3], b[2], b[3]);
            ++stage;
        }
        {
            uint32_t b0 = 0u, b1_ = 0u;
            if (bvalid) { b0 = lds32(baddr + 192); b1_ = lds32(baddr + 208); }
            mbar_wait(bar_full + stage * 8, ph, flag);
            const uint32_t base = sbase + stage * STAGE_BYTES;
            uint32_t a[2][4];
            ldsm_x4_t(a[0], base + offW0);
            ldsm_x4_t(a[1], base + offW1);
            mma16816(acc0, a[0], b0, b1_);
            mma16816(acc1, a[1], b0, b1_);
            ++stage;
        }
        if (t < 2) {
            unsigned int* p = scr + G_B + dst_off;
            st2(p, enc(acc0[0], tag), enc(acc0[1], tag));
            st2(p + 1024, enc(acc0[2], tag), enc(acc0[3], tag));
            st2(p + 2048, enc(acc1[0], tag), enc(acc1[1], tag));
            st2(p + 3072, enc(acc1[2], tag), enc(acc1[3], tag));
        }
        bar_arrive(BAR_B, 288);
    }
    PROFW(0, 9);
    {
        bar_sync(BAR_OS, 384);
        PROFW(0, 10);
        float acc0[4] = {0.f, 0.f, 0.f, 0.f}, acc1[4] = {0.f, 0.f, 0.f, 0.f};
        const uint32_t baddr = sbase + SM_OS + (g & 3) * FR_STRIDE + t * 8;
#pragma unroll 1
        for (int j = 0; j < 4; j++) {
            uint2 b0 = make_uint2(0u, 0u), b1_ = make_uint2(0u, 0u);
            if (bvalid) { b0 = lds64(baddr + j * 64); b1_ = lds64(baddr + j * 64 + 32); }
            mbar_wait(bar_full + stage * 8, ph, flag);
            const uint32_t base = sbase + stage * STAGE_BYTES;
            uint32_t a[4][4];
            ldsm_x4_t(a[0], base + offW0);
            ldsm_x4_t(a[1], base + offW1);
            ldsm_x4_t(a[2], base + 8192 + offW0);
            ldsm_x4_t(a[3], base + 8192 + offW1);
            mma16816(acc0, a[0], b0.x, b0.y);
            mma16816(acc1, a[1], b0.x, b0.y);
            mma16816(acc0, a[2], b1_.x, b1_.y);
            mma16816(acc1, a[3], b1_.x, b1_.y);
            ++stage;
        }
        if (t < 2) {
            unsigned int* p = scr + G_A + dst_off;
            st2(p, enc(acc0[0], tag), enc(acc0[1], tag));
            st2(p + 1024, enc(acc0[2], tag), enc(acc0[3], tag));
            st2(p + 2048, enc(acc1[0], tag), enc(acc1[1], tag));
            st2(p + 3072, enc(acc1[2], tag), enc(acc1[3], tag));
        }
    }
    PROFW(0, 11);
    bar_arrive(BAR_A, 288);
}

typedef CUresult (*EncodeFn)(CUtensorMap*, CUtensorMapDataType, cuuint32_t, void*, const cuuint64_t*, const cuuint64_t*,
                             const cuuint32_t*, const cuuint32_t*, CUtensorMapInterleave, CUtensorMapSwizzle,
                             CUtensorMapL2promotion, CUtensorMapFloatOOBfill);

void make_2d(EncodeFn enc_fn, CUtensorMap* tm, void* base, uint64_t cols, uint64_t rows, uint32_t box_rows) {
    cuuint64_t gd[2] = {cols, rows};
    cuuint64_t gs[1] = {cols * 2};
    cuuint32_t bd[2] = {64, box_rows};
    cuuint32_t es[2] = {1, 1};
    enc_fn(tm, CU_TENSOR_MAP_DATA_TYPE_BFLOAT16, 2, base, gd, gs, bd, es, CU_TENSOR_MAP_INTERLEAVE_NONE,
           CU_TENSOR_MAP_SWIZZLE_128B, CU_TENSOR_MAP_L2_PROMOTION_L2_128B, CU_TENSOR_MAP_FLOAT_OOB_FILL_NONE);
}
void make_3d(EncodeFn enc_fn, CUtensorMap* tm, void* base, uint64_t cols, uint64_t rows, uint32_t box_rows, uint32_t box_blocks) {
    cuuint64_t gd[3] = {64, rows, cols / 64};
    cuuint64_t gs[2] = {cols * 2, 128};
    cuuint32_t bd[3] = {64, box_rows, box_blocks};
    cuuint32_t es[3] = {1, 1, 1};
    enc_fn(tm, CU_TENSOR_MAP_DATA_TYPE_BFLOAT16, 3, base, gd, gs, bd, es, CU_TENSOR_MAP_INTERLEAVE_NONE,
           CU_TENSOR_MAP_SWIZZLE_128B, CU_TENSOR_MAP_L2_PROMOTION_L2_128B, CU_TENSOR_MAP_FLOAT_OOB_FILL_NONE);
}

}

extern "C" void kernel_launch(void* const* d_in, const int* in_sizes, int n_in, void* d_out, int out_size) {
    (void)in_sizes; (void)n_in; (void)out_size;
    static TMaps maps;
    static void* cached[6] = {nullptr, nullptr, nullptr, nullptr, nullptr, nullptr};
    static EncodeFn enc_fn = nullptr;
    static void* scr = nullptr;
    if (!enc_fn) {
        cudaGetSymbolAddress(&scr, g_scratch);
        void* fn = nullptr;
        cudaDriverEntryPointQueryResult qr;
        cudaGetDriverEntryPoint("cuTensorMapEncodeTiled", &fn, cudaEnableDefault, &qr);
        enc_fn = (EncodeFn)fn;
        cudaFuncSetAttribute(fused_kernel, cudaFuncAttributeMaxDynamicSharedMemorySize, SM_ALLOC);
    }
    void* cur[6] = {d_in[3], d_in[6], d_in[1], d_in[2], d_in[8], d_in[4]};
    bool same = true;
    for (int i = 0; i < 6; i++) same = same && (cur[i] == cached[i]);
    if (!same) {
        make_2d(enc_fn, &maps.wq, d_in[3], 4096, 1024, 128);
        make_2d(enc_fn, &maps.w1, d_in[6], F_DIM, 1024, 128);
        make_3d(enc_fn, &maps.k, d_in[1], 128, 16 * SK, 64, 2);
        make_3d(enc_fn, &maps.v, d_in[2], 128, 16 * SK, 64, 2);
        make_3d(enc_fn, &maps.w2, d_in[8], 1024, F_DIM, 16, 4);
        make_3d(enc_fn, &maps.wo, d_in[4], 1024, 4096, 16, 4);
        for (int i = 0; i < 6; i++) cached[i] = cur[i];
    }
    fused_kernel<<<NCTA, NTHREADS, SM_ALLOC, cudaStreamPerThread>>>(
        (const __nv_bfloat16*)d_in[3], (const __nv_bfloat16*)d_in[0], (unsigned int*)scr, (__nv_bfloat16*)d_out,
        (const __nv_bfloat16*)d_in[10], (const __nv_bfloat16*)d_in[7], maps, (const __nv_bfloat16*)d_in[9]);
}
```

```cpp
#include <cuda_runtime.h>
#include <cuda.h>
#include <cuda_bf16.h>
#include <stdint.h>

namespace {

constexpr int NSTAGE = 12;
constexpr int STAGE_BYTES = 16384;

constexpr int D_MODEL = 1024;
constexpr int F_DIM = 3584;
constexpr int SK = 8192;

constexpr int XS_STRIDE = 1032 * 2;
constexpr int FR_STRIDE = 288;

#define PACE_T 652
#define PACE_LEAD 2
#define PACE_OFF PACE_T
#define PW_J 6
#define PACE_CAP 4
#define FP_GAP 160
#define OG_DELAY 400

constexpr int BAR_INIT = 0;
constexpr int BAR_CONS = 1;
constexpr int BAR_PAIR = 2;
constexpr int BAR_X = 6;
constexpr int BAR_ML = 7;
constexpr int BAR_O = 8;
constexpr int BAR_OS = 9;
constexpr int BAR_W1 = 10;
constexpr int BAR_HS = 11;
constexpr int BAR_A = 12;
constexpr int BAR_B = 13;
constexpr int BAR_F = 14;

struct TMaps {
    CUtensorMap wq, w1, k, v, w2, wo, w2n, w1n, wq3, won;
};

__device__ __forceinline__ uint32_t smem_u32(const void* p) { return (uint32_t)__cvta_generic_to_shared(p); }
__device__ __forceinline__ uint32_t gtime32() { uint32_t t; asm volatile("mov.u32 %0, %globaltimer_lo;" : "=r"(t)); return t; }

__device__ __forceinline__ void mbar_init(uint32_t bar, uint32_t cnt) {
    asm volatile("mbarrier.init.shared::cta.b64 [%0], %1;" ::"r"(bar), "r"(cnt) : "memory");
}
__device__ __forceinline__ void mbar_expect_tx(uint32_t bar, uint32_t bytes) {
    asm volatile("mbarrier.arrive.expect_tx.shared::cta.b64 _, [%0], %1;" ::"r"(bar), "r"(bytes) : "memory");
}
__device__ __forceinline__ void mbar_arrive_cnt(uint32_t bar, uint32_t cnt) {
    asm volatile("mbarrier.arrive.shared::cta.b64 _, [%0], %1;" ::"r"(bar), "r"(cnt) : "memory");
}
__device__ __forceinline__ bool mbar_try(uint32_t bar, uint32_t parity) {
    uint32_t ok;
    asm volatile(
        "{\n.reg .pred p;\n"
        "mbarrier.try_wait.parity.shared::cta.b64 p, [%1], %2;\n"
        "selp.u32 %0, 1, 0, p;\n}\n"
        : "=r"(ok)
        : "r"(bar), "r"(parity)
        : "memory");
    return ok != 0;
}
__device__ __noinline__ void mbar_wait_slow(uint32_t bar, uint32_t parity, volatile uint32_t* flag) {
    long long t0 = clock64();
    for (uint32_t it = 0; it < 0x40000000u; it++) {
        if (mbar_try(bar, parity)) return;
        if ((it & 63u) == 63u) {
            if (*flag) return;
            if (clock64() - t0 > 2000000000LL) { *flag = 1u; return; }
        }
    }
}
__device__ __forceinline__ void mbar_wait(uint32_t bar, uint32_t parity, volatile uint32_t* flag) {
    if (mbar_try(bar, parity)) return;
    if (mbar_try(bar, parity)) return;
    mbar_wait_slow(bar, parity, flag);
}

__device__ __forceinline__ void mbar_wait_cluster(uint32_t bar, volatile uint32_t* flag) {
    const long long t0 = clock64();
    for (uint32_t it = 0; it < 0x40000000u; it++) {
        uint32_t ok;
        asm volatile(
            "{\n.reg .pred p;\n"
            "mbarrier.try_wait.parity.acquire.cluster.shared::cta.b64 p, [%1], 0;\n"
            "selp.u32 %0, 1, 0, p;\n}\n"
            : "=r"(ok)
            : "r"(bar)
            : "memory");
        if (ok) return;
        if ((it & 63u) == 63u && (*flag || clock64() - t0 > 4000000000LL)) return;
    }
}

__device__ __forceinline__ void tma_2d(uint32_t dst, const CUtensorMap* tm, int c0, int c1, uint32_t bar) {
    asm volatile(
        "cp.async.bulk.tensor.2d.shared::cluster.global.mbarrier::complete_tx::bytes.L2::cache_hint [%0], [%1, {%3, %4}], [%2], %5;"
        ::"r"(dst), "l"(tm), "r"(bar), "r"(c0), "r"(c1), "l"(0x12F0000000000000ull)
        : "memory");
}
__device__ __forceinline__ void tma_3d(uint32_t dst, const CUtensorMap* tm, int c0, int c1, int c2, uint32_t bar) {
    asm volatile(
        "cp.async.bulk.tensor.3d.shared::cluster.global.mbarrier::complete_tx::bytes.L2::cache_hint [%0], [%1, {%3, %4, %5}], [%2], %6;"
        ::"r"(dst), "l"(tm), "r"(bar), "r"(c0), "r"(c1), "r"(c2), "l"(0x12F0000000000000ull)
        : "memory");
}
__device__ __forceinline__ void bulk_load(uint32_t dst, const void* src, uint32_t bytes, uint32_t bar) {
    asm volatile("cp.async.bulk.shared::cluster.global.mbarrier::complete_tx::bytes [%0], [%1], %2, [%3];"
                 ::"r"(dst), "l"(src), "r"(bytes), "r"(bar)
                 : "memory");
}
__device__ __forceinline__ void prefetch_tmap(const CUtensorMap* tm) {
    asm volatile("prefetch.tensormap [%0];" ::"l"(tm) : "memory");
}
__device__ __forceinline__ void bar_sync(int id, int cnt) { asm volatile("bar.sync %0, %1;" ::"r"(id), "r"(cnt) : "memory"); }
__device__ __forceinline__ void bar_arrive(int id, int cnt) { asm volatile("bar.arrive %0, %1;" ::"r"(id), "r"(cnt) : "memory"); }

__device__ __forceinline__ void ldsm_x4(uint32_t (&r)[4], uint32_t addr) {
    asm volatile("ldmatrix.sync.aligned.m8n8.x4.shared.b16 {%0,%1,%2,%3}, [%4];"
                 : "=r"(r[0]), "=r"(r[1]), "=r"(r[2]), "=r"(r[3])
                 : "r"(addr)
                 : "memory");
}
__device__ __forceinline__ void ldsm_x4_t(uint32_t (&r)[4], uint32_t addr) {
    asm volatile("ldmatrix.sync.aligned.m8n8.x4.trans.shared.b16 {%0,%1,%2,%3}, [%4];"
                 : "=r"(r[0]), "=r"(r[1]), "=r"(r[2]), "=r"(r[3])
                 : "r"(addr)
                 : "memory");
}
__device__ __forceinline__ void mma16816(float (&c)[4], const uint32_t (&a)[4], uint32_t b0, uint32_t b1) {
    asm volatile(
        "mma.sync.aligned.m16n8k16.row.col.f32.bf16.bf16.f32 {%0,%1,%2,%3}, {%4,%5,%6,%7}, {%8,%9}, {%0,%1,%2,%3};"
        : "+f"(c[0]), "+f"(c[1]), "+f"(c[2]), "+f"(c[3])
        : "r"(a[0]), "r"(a[1]), "r"(a[2]), "r"(a[3]), "r"(b0), "r"(b1));
}
__device__ __forceinline__ uint32_t lds32(uint32_t addr) {
    uint32_t v;
    asm volatile("ld.shared.b32 %0, [%1];" : "=r"(v) : "r"(addr) : "memory");
    return v;
}
__device__ __forceinline__ uint2 lds64(uint32_t addr) {
    uint2 v;
    asm volatile("ld.shared.v2.b32 {%0, %1}, [%2];" : "=r"(v.x), "=r"(v.y) : "r"(addr) : "memory");
    return v;
}
__device__ __forceinline__ void sts32(uint32_t addr, uint32_t v) {
    asm volatile("st.shared.b32 [%0], %1;" ::"r"(addr), "r"(v) : "memory");
}
__device__ __forceinline__ void sts64(uint32_t addr, uint32_t a, uint32_t b) {
    asm volatile("st.shared.v2.b32 [%0], {%1, %2};" ::"r"(addr), "r"(a), "r"(b) : "memory");
}

__device__ __forceinline__ float bf16r(float x) { return __bfloat162float(__float2bfloat16_rn(x)); }
__device__ __forceinline__ uint32_t pack_bf16(float lo, float hi) {
    __nv_bfloat162 v = __floats2bfloat162_rn(lo, hi);
    return *reinterpret_cast<uint32_t*>(&v);
}
__device__ __forceinline__ float bf_lo(uint32_t u) { return __uint_as_float(u << 16); }
__device__ __forceinline__ float bf_hi(uint32_t u) { return __uint_as_float(u & 0xffff0000u); }

__device__ __forceinline__ uint32_t enc(float v, uint32_t tag) { return (__float_as_uint(v) & ~3u) | tag; }
__device__ __forceinline__ float dec(uint32_t u) { return __uint_as_float(u & ~3u); }
__device__ __forceinline__ void st2(unsigned int* p, uint32_t a, uint32_t b) {
    asm volatile("st.relaxed.gpu.global.v2.b32 [%0], {%1, %2};" ::"l"(p), "r"(a), "r"(b) : "memory");
}
__device__ __forceinline__ void st4(unsigned int* p, uint32_t a, uint32_t b, uint32_t c, uint32_t d) {
    asm volatile("st.relaxed.gpu.global.v4.b32 [%0], {%1, %2, %3, %4};" ::"l"(p), "r"(a), "r"(b), "r"(c), "r"(d) : "memory");
}
__device__ __forceinline__ uint32_t ld1(const unsigned int* p) {
    uint32_t v;
    asm volatile("ld.relaxed.gpu.global.b32 %0, [%1];" : "=r"(v) : "l"(p) : "memory");
    return v;
}
__device__ __forceinline__ uint2 ld2(const unsigned int* p) {
    uint2 v;
    asm volatile("ld.relaxed.gpu.global.v2.b32 {%0, %1}, [%2];" : "=r"(v.x), "=r"(v.y) : "l"(p) : "memory");
    return v;
}
__device__ __forceinline__ uint4 ld4(const unsigned int* p) {
    uint4 v;
    asm volatile("ld.relaxed.gpu.global.v4.b32 {%0, %1, %2, %3}, [%4];" : "=r"(v.x), "=r"(v.y), "=r"(v.z), "=r"(v.w) : "l"(p) : "memory");
    return v;
}
__device__ __forceinline__ uint32_t bad4(const uint4& v, uint32_t tag) { return (v.x ^ tag) | (v.y ^ tag) | (v.z ^ tag) | (v.w ^ tag); }
__device__ __forceinline__ bool warp_ok(uint32_t bad) { return __all_sync(0xffffffffu, (bad & 3u) == 0u); }
__device__ __forceinline__ void spin_cycles(int n) {
    const uint32_t t0 = (uint32_t)clock64();
    for (int it = 0; it < 1000 && (int)((uint32_t)clock64() - t0) < n; it++) {}
}
constexpr uint32_t POLL_LIMIT = 1u << 21;

__device__ __forceinline__ void gemv_tile4(float (&acc0)[4], float (&acc1)[4], uint32_t a_addr, uint32_t b_addr, bool bvalid) {
    uint32_t a[4][4];
    uint32_t b[4][2];
#pragma unroll
    for (int ks = 0; ks < 4; ks++) ldsm_x4_t(a[ks], a_addr + ks * 2048);
#pragma unroll
    for (int ks = 0; ks < 4; ks++) {
        b[ks][0] = bvalid ? lds32(b_addr + ks * 32) : 0u;
        b[ks][1] = bvalid ? lds32(b_addr + ks * 32 + 16) : 0u;
    }
#pragma unroll
    for (int ks = 0; ks < 4; ks++) {
        if (ks & 1) mma16816(acc1, a[ks], b[ks][0], b[ks][1]);
        else mma16816(acc0, a[ks], b[ks][0], b[ks][1]);
    }
}

template <int N>
__device__ __forceinline__ float final_sum(const unsigned int* buf, int lane, uint32_t tag, bool backoff) {
    const unsigned int* p = buf + (lane >> 3) * (N * 32) + (lane & 7) * 4;
    uint4 d[N];
    for (uint32_t it = 0; it < POLL_LIMIT; it++) {
        uint32_t bad = 0;
#pragma unroll
        for (int i = 0; i < N; i++) { d[i] = ld4(p + i * 32); bad |= bad4(d[i], tag); }
        if (warp_ok(bad)) break;
        if (backoff) __nanosleep(100);
    }
    float s0 = 0.f, s1 = 0.f, s2 = 0.f, s3 = 0.f;
#pragma unroll
    for (int i = 0; i < N; i++) { s0 += dec(d[i].x); s1 += dec(d[i].y); s2 += dec(d[i].z); s3 += dec(d[i].w); }
    const bool hi = lane & 16;
    float u0 = hi ? s0 : s2, u1 = hi ? s1 : s3;
    float k0 = hi ? s2 : s0, k1 = hi ? s3 : s1;
    k0 += __shfl_xor_sync(0xffffffffu, u0, 16);
    k1 += __shfl_xor_sync(0xffffffffu, u1, 16);
    const bool od = lane & 8;
    const float w = od ? k0 : k1;
    float r = od ? k1 : k0;
    r += __shfl_xor_sync(0xffffffffu, w, 8);
    return r;
}

namespace fb {

constexpr int NCTA = 128;
constexpr int NTHREADS = 416;

constexpr int SM_P = NSTAGE * STAGE_BYTES;
constexpr int SM_XS = SM_P;
constexpr int SM_YS = SM_P + 16384;
constexpr int SM_QS = SM_YS + 4160;
constexpr int SM_OS = SM_QS + 2304;
constexpr int SM_HS = SM_OS + 1152;
constexpr int SM_RED = SM_HS + 960;
constexpr int SM_MX = SM_RED + 2048;
constexpr int SM_LS = SM_MX + 256;
constexpr int SM_F = SM_LS + 256;
constexpr int SM_BAR = SM_F + 32;
constexpr int SM_FLAG = SM_BAR + 2 * NSTAGE * 8;
constexpr int SM_TOTAL = SM_FLAG + 8;
constexpr int SM_ALLOC = SM_TOTAL + 1024;

constexpr int YS_STRIDE = 520 * 2;
constexpr int HS_STRIDE = 240;

constexpr int G_EPOCH = 0;
constexpr int G_Q = G_EPOCH + NCTA * 4;
constexpr int G_H = G_Q + 2 * 4 * 4096;
constexpr int G_ML = G_H + 2 * F_DIM * 4;
constexpr int G_O = G_ML + NCTA * 16;
constexpr int G_A = G_O + NCTA * 1024;
constexpr int G_B = G_A + NCTA * 1024;
constexpr int G_TOTAL = G_B + NCTA * 1024;
__device__ __align__(1024) unsigned int g_scratch[G_TOTAL];

__global__ void __launch_bounds__(NTHREADS, 1)
fused_kernel(const __nv_bfloat16* __restrict__ wq, const __nv_bfloat16* __restrict__ x, unsigned int* __restrict__ scr,
             __nv_bfloat16* __restrict__ out, const __nv_bfloat16* __restrict__ gate_w, const __nv_bfloat16* __restrict__ b1,
             const __grid_constant__ TMaps maps, const __nv_bfloat16* __restrict__ b2) {
    extern __shared__ unsigned char smem_raw[];
    const uint32_t sbase = (smem_u32(smem_raw) + 1023u) & ~1023u;
    unsigned char* sptr = smem_raw + (sbase - smem_u32(smem_raw));
    volatile uint32_t* flag = reinterpret_cast<volatile uint32_t*>(sptr + SM_FLAG);

    const int c = blockIdx.x;
    const int tid = threadIdx.x;
    const int warp = tid >> 5;
    const int lane = tid & 31;
    const bool has_w1 = c < 112;
    const int kb = c >> 2, nb = c & 3;
    const uint32_t bar_full = sbase + SM_BAR;
    const uint32_t bar_empty = sbase + SM_BAR + NSTAGE * 8;

    if (warp == 8) {
        const int n_w1 = has_w1 ? 4 : 0;
        const int n_tiles = 44 + n_w1;
        const int kv_row0 = (c >> 3) * SK + (c & 7) * 1024;
        uint32_t due = 0;
        if (lane == 0) {
#pragma unroll
            for (int j = 0; j < PACE_LEAD; j++) mbar_init(bar_full + j * 8, 1);
            asm volatile("fence.mbarrier_init.release.cluster;" ::: "memory");
            asm volatile("fence.proxy.async.shared::cta;" ::: "memory");
#pragma unroll
            for (int j = 0; j < PACE_LEAD; j++) {
                mbar_expect_tx(bar_full + j * 8, STAGE_BYTES);
                tma_2d(sbase + j * STAGE_BYTES, &maps.wq, (c >> 1) * 64, (c & 1) * 512 + j * 128, bar_full + j * 8);
            }
            due = gtime32() + PACE_OFF + (c >> 1) * PACE_T / 64;
#pragma unroll
            for (int i = PACE_LEAD; i < NSTAGE; i++) mbar_init(bar_full + i * 8, 1);
#pragma unroll
            for (int i = 0; i < NSTAGE; i++) mbar_init(bar_empty + i * 8, 8);
            *flag = 0u;
            asm volatile("fence.mbarrier_init.release.cluster;" ::: "memory");
            asm volatile("fence.proxy.async.shared::cta;" ::: "memory");
            prefetch_tmap(&maps.w1);
            prefetch_tmap(&maps.k);
            prefetch_tmap(&maps.v);
            prefetch_tmap(&maps.w2);
            prefetch_tmap(&maps.wo);
        }
        __syncwarp();
        bar_arrive(BAR_INIT, NTHREADS);
        if (lane == 0) {
            int landed = 0;
            for (int i = PACE_LEAD; i < n_tiles; i++) {
                while (landed + PACE_CAP <= i) {
                    mbar_wait(bar_full + (landed % NSTAGE) * 8, (uint32_t)(landed / NSTAGE) & 1u, flag);
                    landed++;
                }
                const int stage = i % NSTAGE;
                if (i >= NSTAGE) mbar_wait(bar_empty + stage * 8, (uint32_t)(i / NSTAGE - 1) & 1u, flag);
                for (int it = 0; it < 100000 && (int)(gtime32() - due) < 0; it++) {}
                const uint32_t dst = sbase + stage * STAGE_BYTES;
                const uint32_t fb = bar_full + stage * 8;
                int j = i - 4;
                if (j < 0) {
                    mbar_expect_tx(fb, STAGE_BYTES);
                    tma_2d(dst, &maps.wq, (c >> 1) * 64, (c & 1) * 512 + i * 128, fb);
                    due += (j == -1 && !has_w1) ? PACE_T * 9 / 2 : PACE_T;
                } else if (j < n_w1) {
                    mbar_expect_tx(fb, STAGE_BYTES);
                    tma_2d(dst, &maps.w1, (c >> 1) * 64, (c & 1) * 512 + j * 128, fb);
                    due += PACE_T * 7 / 8;
                } else if (j < 32 + n_w1) {
                    j -= n_w1;
                    mbar_expect_tx(fb, STAGE_BYTES);
                    tma_3d(dst, j < 16 ? &maps.k : &maps.v, 0, kv_row0 + (j & 15) * 64, 0, fb);
                    due += PACE_T;
                } else {
                    j -= 32 + n_w1;
                    const CUtensorMap* tm = j < 4 ? &maps.w2 : &maps.wo;
                    const int row = j < 4 ? kb * 112 + j * 32 : kb * 128 + (j - 4) * 32;
                    mbar_expect_tx(fb, j != 3 ? STAGE_BYTES : STAGE_BYTES / 2);
                    tma_3d(dst, tm, 0, row, nb * 4, fb);
                    if (j != 3) tma_3d(dst + 8192, tm, 0, row + 16, nb * 4, fb);
                    due += j != 3 ? PACE_T : PACE_T / 2;
                }
            }
        }
        return;
    }

    const int g = lane >> 2;
    const int t = lane & 3;
    const int khalf = c & 1;
    const int pair = c >> 3;
    const int mt = warp & 3;
    const int kh2 = warp >> 2;
    const uint32_t epoch = ld1(scr + G_EPOCH + c * 4) + 1u;
    unsigned int* const q_dst = scr + G_Q + (khalf * 4 + 2 * t) * 4096 + (c >> 1) * 64 + mt * 16 + 2 * g;
    unsigned int* const h_dst = scr + G_H + (khalf * F_DIM + (c >> 1) * 64 + mt * 16 + g) * 4 + 2 * t;
    if (warp < 8) {
        asm volatile("prefetch.global.L2 [%0];" ::"l"(wq + (size_t)(khalf * 512 + tid) * 4096 + (c >> 1) * 64));
        const uint4 x0 = __ldg(reinterpret_cast<const uint4*>(x) + tid);
        const uint4 x1 = __ldg(reinterpret_cast<const uint4*>(x) + 256 + tid);
        if (warp < 4 && t < 2) {
            st2(q_dst, 0u, 0u);
            st2(q_dst + 4096, 0u, 0u);
            if (has_w1) {
                st2(h_dst, 0u, 0u);
                st2(h_dst + 32, 0u, 0u);
            }
        }
        *reinterpret_cast<uint4*>(sptr + SM_XS + (tid >> 7) * XS_STRIDE + (tid & 127) * 16) = x0;
        *reinterpret_cast<uint4*>(sptr + SM_XS + (2 + (tid >> 7)) * XS_STRIDE + (tid & 127) * 16) = x1;
    }
    const uint32_t tag = 1u + epoch % 3u;

    if (warp >= 9) {
        float gate = 0.f, b2v = 0.f;
        if (warp == 9) {
            uint4 gw[4];
#pragma unroll
            for (int i = 0; i < 4; i++) gw[i] = __ldg(reinterpret_cast<const uint4*>(gate_w) + i * 32 + lane);
            b2v = __bfloat162float(b2[c * 8 + (lane & 7)]);
            bar_sync(BAR_INIT, NTHREADS);
            float zz = 0.f;
#pragma unroll 1
            for (int b = 0; b < 4; b++) {
                float zs = 0.f;
#pragma unroll
                for (int i = 0; i < 4; i++) {
                    const uint4 xv = *reinterpret_cast<const uint4*>(sptr + SM_XS + b * XS_STRIDE + (i * 32 + lane) * 16);
                    const uint32_t xa[4] = {xv.x, xv.y, xv.z, xv.w};
                    const uint32_t wa[4] = {gw[i].x, gw[i].y, gw[i].z, gw[i].w};
#pragma unroll
                    for (int e = 0; e < 4; e++) {
                        zs += bf16r(bf_lo(xa[e]) * bf_lo(wa[e]));
                        zs += bf16r(bf_hi(xa[e]) * bf_hi(wa[e]));
                    }
                }
#pragma unroll
                for (int o = 16; o > 0; o >>= 1) zs += __shfl_xor_sync(0xffffffffu, zs, o);
                if ((lane >> 3) == b) zz = zs;
            }
            bar_arrive(BAR_X, 288);
            zz = bf16r(zz);
            gate = bf16r(1.0f / (1.0f + __expf(-zz)));
            if (lane == 0) *reinterpret_cast<volatile unsigned int*>(scr + G_EPOCH + c * 4) = epoch;
        } else if (warp == 11) {
            const bool has4 = lane < 16;
            float bias[4];
#pragma unroll
            for (int i = 0; i < 4; i++) bias[i] = (i < 3 || has4) ? __bfloat162float(b1[kb * 112 + i * 32 + lane]) : 0.f;
            bar_sync(BAR_INIT, NTHREADS);
            bar_sync(BAR_W1, 288);
            const unsigned int* p = scr + G_H + (kb * 112 + lane) * 4;
            uint4 d[4][2];
            for (uint32_t it = 0; it < POLL_LIMIT; it++) {
                __nanosleep(1000);
                uint32_t bad = 0;
#pragma unroll
                for (int i = 0; i < 4; i++) {
                    if (i < 3 || has4) {
                        d[i][0] = ld4(p + i * 128);
                        d[i][1] = ld4(p + i * 128 + F_DIM * 4);
                        bad |= bad4(d[i][0], tag) | bad4(d[i][1], tag);
                    }
                }
                if (warp_ok(bad)) break;
            }
#pragma unroll
            for (int i = 0; i < 4; i++) {
                if (i < 3 || has4) {
                    const int cl = i * 32 + lane;
                    const uint32_t u0[4] = {d[i][0].x, d[i][0].y, d[i][0].z, d[i][0].w};
                    const uint32_t u1[4] = {d[i][1].x, d[i][1].y, d[i][1].z, d[i][1].w};
#pragma unroll
                    for (int b = 0; b < 4; b++) {
                        float v = bf16r(dec(u0[b]) + dec(u1[b]));
                        v = bf16r(v + bias[i]);
                        const float inner = 0.7978845608028654f * (v + 0.044715f * v * v * v);
                        const float hv = 0.5f * v * (1.0f + tanhf(inner));
                        *reinterpret_cast<__nv_bfloat16*>(sptr + SM_HS + b * HS_STRIDE + cl * 2) = __float2bfloat16_rn(hv);
                    }
                }
            }
            bar_arrive(BAR_HS, 288);
        } else if (warp == 12) {
            bar_sync(BAR_INIT, NTHREADS);
            bar_sync(BAR_ML, 64);
            const unsigned int* p = scr + G_ML + pair * 128 + lane * 4;
            uint4 d;
            for (uint32_t it = 0; it < POLL_LIMIT; it++) {
                __nanosleep(1000);
                d = ld4(p);
                if (warp_ok(bad4(d, tag))) break;
            }
            const float m0 = dec(d.x), m1 = dec(d.z);
            float M0 = m0, M1 = m1;
#pragma unroll
            for (int o = 4; o < 32; o <<= 1) {
                M0 = fmaxf(M0, __shfl_xor_sync(0xffffffffu, M0, o));
                M1 = fmaxf(M1, __shfl_xor_sync(0xffffffffu, M1, o));
            }
            const float w0 = exp2f((m0 - M0) * 1.4426950408889634f), w1 = exp2f((m1 - M1) * 1.4426950408889634f);
            float L0 = w0 * dec(d.y), L1 = w1 * dec(d.w);
#pragma unroll
            for (int o = 4; o < 32; o <<= 1) {
                L0 += __shfl_xor_sync(0xffffffffu, L0, o);
                L1 += __shfl_xor_sync(0xffffffffu, L1, o);
            }
            if (g == (c & 7)) *reinterpret_cast<float2*>(sptr + SM_F + t * 8) = make_float2(w0 / L0, w1 / L1);
            bar_arrive(BAR_F, 288);
        } else {
            bar_sync(BAR_INIT, NTHREADS);
        }
        {
            const int hb = warp - 9;
            const unsigned int* po = scr + G_O + ((hb * 4 + (kb >> 3)) * 8 + (kb & 7)) * 1024 + lane * 4;
            uint4 d[8];
            uint32_t pend = 0xffu;
            bar_sync(BAR_O, 384);
            __nanosleep(OG_DELAY);
            for (uint32_t it = 0; it < POLL_LIMIT; it++) {
#pragma unroll
                for (int s = 0; s < 8; s++)
                    if (pend & (1u << s)) d[s] = ld4(po + s * 128);
#pragma unroll
                for (int s = 0; s < 8; s++)
                    if ((pend & (1u << s)) && warp_ok(bad4(d[s], tag))) pend &= ~(1u << s);
                if (pend == 0u) break;
                __nanosleep(100);
            }
            float o0 = 0.f, o1 = 0.f, o2 = 0.f, o3 = 0.f;
#pragma unroll
            for (int s = 0; s < 8; s++) {
                o0 += dec(d[s].x);
                o1 += dec(d[s].y);
                o2 += dec(d[s].z);
                o3 += dec(d[s].w);
            }
            sts64(sbase + SM_OS + hb * FR_STRIDE + lane * 8, pack_bf16(o0, o2), pack_bf16(o1, o3));
            bar_arrive(BAR_OS, 384);
        }
        if (warp != 9) return;
        bar_sync(BAR_B, 288);
        const float bv = bf16r(bf16r(final_sum<8>(scr + G_B + c * 1024, lane, tag, true)) + b2v);
        const float bterm = bf16r(bf16r(1.0f - gate) * bv);
        bar_sync(BAR_A, 288);
        const float aterm = bf16r(gate * bf16r(final_sum<8>(scr + G_A + c * 1024, lane, tag, false)));
        out[(lane >> 3) * D_MODEL + c * 8 + (lane & 7)] = __float2bfloat16_rn(aterm + bterm);
        return;
    }

    bar_sync(BAR_INIT, NTHREADS);

    int stage = 0;
    uint32_t ph = 0;
    const uint32_t l8 = lane & 7;
    const uint32_t rowT = (l8 + 8 * (lane >> 4)) * 128;
    const uint32_t offT = rowT + ((((uint32_t)(2 * mt + ((lane >> 3) & 1))) ^ l8) << 4);
    const bool bvalid = g < 4;
    const int dst_off = ((nb * 32 + warp * 4) * 32 + kb) * 32 + g * 4 + 2 * t;

    {
        float acc0[4] = {0.f, 0.f, 0.f, 0.f}, acc1[4] = {0.f, 0.f, 0.f, 0.f};
        const uint32_t baddr = sbase + SM_XS + (g & 3) * XS_STRIDE + (khalf * 512 + kh2 * 64 + 2 * t) * 2;
#pragma unroll 1
        for (int j = 0; j < 4; j++) {
            mbar_wait(bar_full + stage * 8, ph, flag);
            gemv_tile4(acc0, acc1, sbase + stage * STAGE_BYTES + kh2 * 8192 + offT, baddr + j * 256, bvalid);
            __syncwarp();
            if (lane == 0) mbar_arrive_cnt(bar_empty + stage * 8, 1);
            ++stage;
        }
        float4* red = reinterpret_cast<float4*>(sptr + SM_RED) + mt * 16 + (g * 2 + (t & 1));
        if (kh2 == 1 && t < 2) *red = make_float4(acc0[0] + acc1[0], acc0[1] + acc1[1], acc0[2] + acc1[2], acc0[3] + acc1[3]);
        bar_sync(BAR_PAIR + mt, 64);
        if (kh2 == 0 && t < 2) {
            const float4 o = *red;
            st2(q_dst, enc(acc0[0] + acc1[0] + o.x, tag), enc(acc0[2] + acc1[2] + o.z, tag));
            st2(q_dst + 4096, enc(acc0[1] + acc1[1] + o.y, tag), enc(acc0[3] + acc1[3] + o.w, tag));
        }
    }
    if (has_w1) {
        {
            uint4 xv[4];
#pragma unroll
            for (int i = 0; i < 4; i++) xv[i] = *reinterpret_cast<const uint4*>(sptr + SM_XS + mt * XS_STRIDE + (i * 32 + lane) * 16);
            const uint4 xs = *reinterpret_cast<const uint4*>(sptr + SM_XS + mt * XS_STRIDE + (khalf * 64 + kh2 * 32 + lane) * 16);
            float s0 = 0.f, s1 = 0.f;
#pragma unroll
            for (int i = 0; i < 4; i++) {
                const uint32_t xa[4] = {xv[i].x, xv[i].y, xv[i].z, xv[i].w};
#pragma unroll
                for (int e = 0; e < 4; e++) { s0 += bf_lo(xa[e]); s1 += bf_hi(xa[e]); }
            }
            float s = s0 + s1;
#pragma unroll
            for (int o = 16; o > 0; o >>= 1) s += __shfl_xor_sync(0xffffffffu, s, o);
            const float mean = s * (1.0f / 1024.0f);
            float q0 = 0.f, q1 = 0.f;
#pragma unroll
            for (int i = 0; i < 4; i++) {
                const uint32_t xa[4] = {xv[i].x, xv[i].y, xv[i].z, xv[i].w};
#pragma unroll
                for (int e = 0; e < 4; e++) {
                    const float d0 = bf_lo(xa[e]) - mean, d1 = bf_hi(xa[e]) - mean;
                    q0 = fmaf(d0, d0, q0);
                    q1 = fmaf(d1, d1, q1);
                }
            }
            float q = q0 + q1;
#pragma unroll
            for (int o = 16; o > 0; o >>= 1) q += __shfl_xor_sync(0xffffffffu, q, o);
            const float mb = bf16r(mean);
            const float vb = bf16r(q * (1.0f / 1024.0f));
            const float den = bf16r(sqrtf(bf16r(vb + 1e-5f)));
            const uint32_t xa[4] = {xs.x, xs.y, xs.z, xs.w};
            uint32_t ya[4];
#pragma unroll
            for (int e = 0; e < 4; e++) ya[e] = pack_bf16(bf16r(bf_lo(xa[e]) - mb) / den, bf16r(bf_hi(xa[e]) - mb) / den);
            *reinterpret_cast<uint4*>(sptr + SM_YS + mt * YS_STRIDE + (kh2 * 32 + lane) * 16) = make_uint4(ya[0], ya[1], ya[2], ya[3]);
            bar_sync(BAR_CONS, 256);
        }
        float acc0[4] = {0.f, 0.f, 0.f, 0.f}, acc1[4] = {0.f, 0.f, 0.f, 0.f};
        const uint32_t baddr = sbase + SM_YS + (g & 3) * YS_STRIDE + (kh2 * 64 + 2 * t) * 2;
#pragma unroll 1
        for (int j = 0; j < 4; j++) {
            mbar_wait(bar_full + stage * 8, ph, flag);
            gemv_tile4(acc0, acc1, sbase + stage * STAGE_BYTES + kh2 * 8192 + offT, baddr + j * 256, bvalid);
            __syncwarp();
            if (lane == 0) mbar_arrive_cnt(bar_empty + stage * 8, 1);
            ++stage;
        }
        float4* red = reinterpret_cast<float4*>(sptr + SM_RED + 1024) + mt * 16 + (g * 2 + (t & 1));
        if (kh2 == 1 && t < 2) *red = make_float4(acc0[0] + acc1[0], acc0[1] + acc1[1], acc0[2] + acc1[2], acc0[3] + acc1[3]);
        bar_sync(BAR_PAIR + mt, 64);
        if (kh2 == 0 && t < 2) {
            const float4 o = *red;
            st2(h_dst, enc(acc0[0] + acc1[0] + o.x, tag), enc(acc0[1] + acc1[1] + o.y, tag));
            st2(h_dst + 32, enc(acc0[2] + acc1[2] + o.z, tag), enc(acc0[3] + acc1[3] + o.w, tag));
        }
    } else {
        mbar_wait(bar_full + stage * 8, ph, flag);
    }
    bar_arrive(BAR_W1, 288);
    uint32_t qf[8][2];
    {
        const unsigned int* p = scr + G_Q + (pair >> 2) * 4096 + (pair & 3) * 1024 + tid * 4;
        uint4 d0, d1;
        for (uint32_t it = 0; it < POLL_LIMIT; it++) {
            d0 = ld4(p);
            d1 = ld4(p + 4 * 4096);
            if (warp_ok(bad4(d0, tag) | bad4(d1, tag))) break;
            __nanosleep(200);
        }
        sts64(sbase + SM_QS + warp * FR_STRIDE + lane * 8,
              pack_bf16(dec(d0.x) + dec(d1.x), dec(d0.z) + dec(d1.z)), pack_bf16(dec(d0.y) + dec(d1.y), dec(d0.w) + dec(d1.w)));
        bar_sync(BAR_CONS, 256);
#pragma unroll
        for (int ks = 0; ks < 8; ks++) {
            const uint2 v = lds64(sbase + SM_QS + g * FR_STRIDE + (ks * 4 + t) * 8);
            qf[ks][0] = v.x;
            qf[ks][1] = v.y;
        }
    }
    float sc[8][4];
    {
        int st = stage + kh2;
        uint32_t php = ph;
        const uint32_t krow = mt * 16 + l8 + 8 * ((lane >> 3) & 1);
        const uint32_t khi = lane >> 4;
#pragma unroll
        for (int i = 0; i < 8; i++) {
            mbar_wait(bar_full + st * 8, php, flag);
            const uint32_t base = sbase + st * STAGE_BYTES + krow * 128;
            float c0[4] = {0.f, 0.f, 0.f, 0.f}, c1[4] = {0.f, 0.f, 0.f, 0.f};
            uint32_t a[8][4];
#pragma unroll
            for (int ks = 0; ks < 8; ks++)
                ldsm_x4(a[ks], base + (ks >> 2) * 8192 + (((uint32_t)((ks & 3) * 2) + khi) ^ l8) * 16);
#pragma unroll
            for (int ks = 0; ks < 8; ks++) {
                if (ks & 1) mma16816(c1, a[ks], qf[ks][0], qf[ks][1]);
                else mma16816(c0, a[ks], qf[ks][0], qf[ks][1]);
            }
            __syncwarp();
            if (lane == 0) mbar_arrive_cnt(bar_empty + st * 8, 2);
#pragma unroll
            for (int e = 0; e < 4; e++) sc[i][e] = bf16r(bf16r(c0[e] + c1[e]) * 0.08838834764831845f);
            st += 2;
            if (st >= NSTAGE) { st -= NSTAGE; php ^= 1u; }
        }
        stage += 16 - NSTAGE;
        ph ^= 1u;
        if (stage >= NSTAGE) { stage -= NSTAGE; ph ^= 1u; }
    }
    {
        float m0 = sc[0][0], m1 = sc[0][1];
#pragma unroll
        for (int i = 0; i < 8; i++) {
            m0 = fmaxf(m0, fmaxf(sc[i][0], sc[i][2]));
            m1 = fmaxf(m1, fmaxf(sc[i][1], sc[i][3]));
        }
#pragma unroll
        for (int o = 4; o < 32; o <<= 1) {
            m0 = fmaxf(m0, __shfl_xor_sync(0xffffffffu, m0, o));
            m1 = fmaxf(m1, __shfl_xor_sync(0xffffffffu, m1, o));
        }
        float2* mx = reinterpret_cast<float2*>(sptr + SM_MX);
        if (g == 0) mx[warp * 4 + t] = make_float2(m0, m1);
        bar_sync(BAR_X, 288);
#pragma unroll
        for (int w = 0; w < 8; w++) {
            const float2 v = mx[w * 4 + t];
            m0 = fmaxf(m0, v.x);
            m1 = fmaxf(m1, v.y);
        }
        float l0 = 0.f, l1 = 0.f;
#pragma unroll
        for (int i = 0; i < 8; i++) {
            const float e0 = exp2f((sc[i][0] - m0) * 1.4426950408889634f);
            const float e1 = exp2f((sc[i][1] - m1) * 1.4426950408889634f);
            const float e2 = exp2f((sc[i][2] - m0) * 1.4426950408889634f);
            const float e3 = exp2f((sc[i][3] - m1) * 1.4426950408889634f);
            l0 += e0 + e2;
            l1 += e1 + e3;
            const uint32_t key = (2 * i + kh2) * 64 + mt * 16 + g;
            sts32(sbase + SM_P + key * 16 + t * 4, pack_bf16(e0, e1));
            sts32(sbase + SM_P + (key + 8) * 16 + t * 4, pack_bf16(e2, e3));
        }
#pragma unroll
        for (int o = 4; o < 32; o <<= 1) {
            l0 += __shfl_xor_sync(0xffffffffu, l0, o);
            l1 += __shfl_xor_sync(0xffffffffu, l1, o);
        }
        float2* ls = reinterpret_cast<float2*>(sptr + SM_LS);
        if (g == 0) ls[warp * 4 + t] = make_float2(l0, l1);
        bar_sync(BAR_CONS, 256);
        if (warp == 0) {
            l0 = 0.f;
            l1 = 0.f;
#pragma unroll
            for (int w = 0; w < 8; w++) {
                const float2 v = ls[w * 4 + t];
                l0 += v.x;
                l1 += v.y;
            }
            if (g == 0) st4(scr + G_ML + c * 16 + t * 4, enc(m0, tag), enc(l0, tag), enc(m1, tag), enc(l1, tag));
            bar_arrive(BAR_ML, 64);
        }
    }
    {
        float acc0[4] = {0.f, 0.f, 0.f, 0.f}, acc1[4] = {0.f, 0.f, 0.f, 0.f};
        const uint32_t paddr = sbase + SM_P + lane * 16;
        unsigned int* p = scr + G_O + ((pair * 8 + 2 * t) * 8 + (c & 7)) * 128 + warp * 16 + 2 * g;
#pragma unroll 1
        for (int j = 0; j < 16; j++) {
            if (j == PW_J) {
                st2(p, 0u, 0u);
                st2(p + 1024, 0u, 0u);
                if (t < 2) {
#pragma unroll
                    for (int e = 0; e < 4; e++) {
                        st2(scr + G_A + dst_off + e * 1024, 0u, 0u);
                        st2(scr + G_B + dst_off + e * 1024, 0u, 0u);
                    }
                }
            }
            uint32_t pb[2][4];
            ldsm_x4_t(pb[0], paddr + j * 1024);
            ldsm_x4_t(pb[1], paddr + j * 1024 + 512);
            mbar_wait(bar_full + stage * 8, ph, flag);
            const uint32_t base = sbase + stage * STAGE_BYTES + kh2 * 8192 + offT;
            uint32_t a[4][4];
#pragma unroll
            for (int ks = 0; ks < 4; ks++) ldsm_x4_t(a[ks], base + ks * 2048);
            mma16816(acc0, a[0], pb[0][0], pb[0][1]);
            mma16816(acc1, a[1], pb[0][2], pb[0][3]);
            mma16816(acc0, a[2], pb[1][0], pb[1][1]);
            mma16816(acc1, a[3], pb[1][2], pb[1][3]);
            __syncwarp();
            if (lane == 0) mbar_arrive_cnt(bar_empty + stage * 8, 1);
            if (++stage == NSTAGE) { stage = 0; ph ^= 1u; }
            if (j == 14) bar_sync(BAR_F, 288);
        }
        const float2 f = *reinterpret_cast<const float2*>(sptr + SM_F + t * 8);
        st2(p, enc((acc0[0] + acc1[0]) * f.x, tag), enc((acc0[2] + acc1[2]) * f.x, tag));
        st2(p + 1024, enc((acc0[1] + acc1[1]) * f.y, tag), enc((acc0[3] + acc1[3]) * f.y, tag));
        bar_arrive(BAR_O, 384);
    }
    const uint32_t offW0 = (warp >> 1) * 2048 + rowT + ((((uint32_t)(4 * (warp & 1) + ((lane >> 3) & 1))) ^ l8) << 4);
    const uint32_t offW1 = (warp >> 1) * 2048 + rowT + ((((uint32_t)(4 * (warp & 1) + 2 + ((lane >> 3) & 1))) ^ l8) << 4);
    {
        bar_sync(BAR_HS, 288);
        float acc0[4] = {0.f, 0.f, 0.f, 0.f}, acc1[4] = {0.f, 0.f, 0.f, 0.f};
        const uint32_t baddr = sbase + SM_HS + (g & 3) * HS_STRIDE + t * 4;
#pragma unroll 1
        for (int j = 0; j < 3; j++) {
            uint32_t b[4] = {0u, 0u, 0u, 0u};
            if (bvalid) {
#pragma unroll
                for (int e = 0; e < 4; e++) b[e] = lds32(baddr + j * 64 + e * 16);
            }
            mbar_wait(bar_full + stage * 8, ph, flag);
            const uint32_t base = sbase + stage * STAGE_BYTES;
            uint32_t a[4][4];
            ldsm_x4_t(a[0], base + offW0);
            ldsm_x4_t(a[1], base + offW1);
            ldsm_x4_t(a[2], base + 8192 + offW0);
            ldsm_x4_t(a[3], base + 8192 + offW1);
            mma16816(acc0, a[0], b[0], b[1]);
            mma16816(acc1, a[1], b[0], b[1]);
            mma16816(acc0, a[2], b[2], b[3]);
            mma16816(acc1, a[3], b[2], b[3]);
            ++stage;
        }
        {
            uint32_t b0 = 0u, b1_ = 0u;
            if (bvalid) { b0 = lds32(baddr + 192); b1_ = lds32(baddr + 208); }
            mbar_wait(bar_full + stage * 8, ph, flag);
            const uint32_t base = sbase + stage * STAGE_BYTES;
            uint32_t a[2][4];
            ldsm_x4_t(a[0], base + offW0);
            ldsm_x4_t(a[1], base + offW1);
            mma16816(acc0, a[0], b0, b1_);
            mma16816(acc1, a[1], b0, b1_);
            ++stage;
        }
        if (t < 2) {
            unsigned int* p = scr + G_B + dst_off;
            st2(p, enc(acc0[0], tag), enc(acc0[1], tag));
            st2(p + 1024, enc(acc0[2], tag), enc(acc0[3], tag));
            st2(p + 2048, enc(acc1[0], tag), enc(acc1[1], tag));
            st2(p + 3072, enc(acc1[2], tag), enc(acc1[3], tag));
        }
        bar_arrive(BAR_B, 288);
    }
    {
        bar_sync(BAR_OS, 384);
        float acc0[4] = {0.f, 0.f, 0.f, 0.f}, acc1[4] = {0.f, 0.f, 0.f, 0.f};
        const uint32_t baddr = sbase + SM_OS + (g & 3) * FR_STRIDE + t * 8;
#pragma unroll 1
        for (int j = 0; j < 4; j++) {
            uint2 b0 = make_uint2(0u, 0u), b1_ = make_uint2(0u, 0u);
            if (bvalid) { b0 = lds64(baddr + j * 64); b1_ = lds64(baddr + j * 64 + 32); }
            mbar_wait(bar_full + stage * 8, ph, flag);
            const uint32_t base = sbase + stage * STAGE_BYTES;
            uint32_t a[4][4];
            ldsm_x4_t(a[0], base + offW0);
            ldsm_x4_t(a[1], base + offW1);
            ldsm_x4_t(a[2], base + 8192 + offW0);
            ldsm_x4_t(a[3], base + 8192 + offW1);
            mma16816(acc0, a[0], b0.x, b0.y);
            mma16816(acc1, a[1], b0.x, b0.y);
            mma16816(acc0, a[2], b1_.x, b1_.y);
            mma16816(acc1, a[3], b1_.x, b1_.y);
            ++stage;
        }
        if (t < 2) {
            unsigned int* p = scr + G_A + dst_off;
            st2(p, enc(acc0[0], tag), enc(acc0[1], tag));
            st2(p + 1024, enc(acc0[2], tag), enc(acc0[3], tag));
            st2(p + 2048, enc(acc1[0], tag), enc(acc1[1], tag));
            st2(p + 3072, enc(acc1[2], tag), enc(acc1[3], tag));
        }
    }
    bar_arrive(BAR_A, 288);
}

}

namespace c6 {

constexpr int CS = 6;
constexpr int NCL = 16;
constexpr int NCTA = NCL * CS;
constexpr int NTHREADS = 416;
constexpr int NST = 11;

constexpr int SM_P = NST * STAGE_BYTES;
constexpr int SM_XS = SM_P;
constexpr int SM_YS = SM_P + 8256;
constexpr int SM_OS = SM_P;
constexpr int SM_QS = SM_P + 22528;
constexpr int SM_HS = SM_QS + 2304;
constexpr int SM_RED = SM_HS + 5248;
constexpr int SM_MX = SM_RED + 2048;
constexpr int SM_LS = SM_MX + 256;
constexpr int SM_F = SM_LS + 256;
constexpr int SM_G = SM_F + 32;
constexpr int SM_ST = SM_G + 16;
constexpr int SM_OR = SM_ST + 384;
constexpr int SM_XR = SM_OR + 6144;
constexpr int SM_BAR = SM_XR + 6144;
constexpr int SM_FLAG = SM_BAR + (2 * NST + 5) * 8;
constexpr int SM_TOTAL = SM_FLAG + 8;
constexpr int SM_ALLOC = SM_TOTAL + 1024;
constexpr int HS_STRIDE = 1312;
constexpr int OS_STRIDE = 1568;
constexpr int BAR_Y = BAR_X;
constexpr int BAR_HELP = BAR_ML;

#define CAP6 5
#define LEAD6 3
#define OG_GAP 100
#define OG6_DELAY 300
constexpr uint32_t P_B = PACE_T * 192;
constexpr uint32_t P_52 = (uint32_t)((long long)P_B * (316 - 6 * LEAD6) / (6 * (52 - LEAD6)));
constexpr uint32_t P_54 = (uint32_t)((long long)P_B * (316 - 6 * LEAD6) / (6 * (54 - LEAD6)));
#define OFF6 (PACE_T * LEAD6 * 96 / 256)

constexpr int G_EPOCH = 0;
constexpr int G_Q = G_EPOCH + 128 * 4;
constexpr int G_H = G_Q + 2 * 4 * 4096;
constexpr int G_O = G_H + 2 * 4 * 4096;
constexpr int G_TOTAL = G_O + 4 * 4096;
__device__ __align__(1024) unsigned int g_scratch[G_TOTAL];

#define KTW(w, i)
#define KTA(i)

__device__ __forceinline__ void load_b(uint2 (&b)[4], uint32_t b_addr, bool bvalid) {
#pragma unroll
    for (int ks = 0; ks < 4; ks++) b[ks] = bvalid ? lds64(b_addr + ks * 32) : make_uint2(0u, 0u);
}
__device__ __forceinline__ void st_async2(uint32_t addr, float a, float b, uint32_t bar) {
    asm volatile("st.async.weak.shared::cluster.mbarrier::complete_tx::bytes.v2.f32 [%0], {%1, %2}, [%3];"
                 ::"r"(addr), "f"(a), "f"(b), "r"(bar) : "memory");
}
__device__ __forceinline__ void st_async4(uint32_t addr, float a, float b, float c, float d, uint32_t bar) {
    asm volatile("st.async.weak.shared::cluster.mbarrier::complete_tx::bytes.v4.f32 [%0], {%1, %2, %3, %4}, [%5];"
                 ::"r"(addr), "f"(a), "f"(b), "f"(c), "f"(d), "r"(bar) : "memory");
}
__device__ __forceinline__ uint32_t mapa(uint32_t addr, uint32_t rank) {
    uint32_t r;
    asm volatile("mapa.shared::cluster.u32 %0, %1, %2;" : "=r"(r) : "r"(addr), "r"(rank));
    return r;
}

__global__ void __launch_bounds__(NTHREADS, 1)
fused_kernel(const __nv_bfloat16* __restrict__ wq, const __nv_bfloat16* __restrict__ x, unsigned int* __restrict__ scr,
             __nv_bfloat16* __restrict__ out, const __nv_bfloat16* __restrict__ gate_w, const __nv_bfloat16* __restrict__ b1,
             const __grid_constant__ TMaps maps, const __nv_bfloat16* __restrict__ b2) {
    extern __shared__ unsigned char smem_raw[];
    const uint32_t sbase = (smem_u32(smem_raw) + 1023u) & ~1023u;
    unsigned char* sptr = smem_raw + (sbase - smem_u32(smem_raw));
    volatile uint32_t* flag = reinterpret_cast<volatile uint32_t*>(sptr + SM_FLAG);

    const int c = blockIdx.x;
    const int tid = threadIdx.x;
    const int warp = tid >> 5;
    const int lane = tid & 31;
    const int cl = c / CS, r = c - cl * CS;
    const int u0 = 8 * cl + (r < 2 ? 2 * r : r + 2);
    const int v0 = 7 * cl + 2 * (r - 2);
    const int nblk = 22 - ((0x0021100 >> (4 * r)) & 3);
    const int n2 = r < 4 ? 5 : 4;
    const int w2_0 = min(5 * r, 24), wo_0 = 5 * r + (r == 5);
    const uint32_t bar_full = sbase + SM_BAR;
    const uint32_t bar_empty = sbase + SM_BAR + NST * 8;
    const uint32_t bar_st = sbase + SM_BAR + 2 * NST * 8;
    const uint32_t bar_or = bar_st + 8;
    const uint32_t bar_xr = bar_st + 24;

    KTW(0, 0);
    if (warp == 8) {
        uint32_t t0 = 0;
        if (lane == 0) {
#pragma unroll
            for (int j = 0; j < LEAD6; j++) mbar_init(bar_full + j * 8, 1);
            asm volatile("fence.mbarrier_init.release.cluster;" ::: "memory");
            asm volatile("fence.proxy.async.shared::cta;" ::: "memory");
#pragma unroll
            for (int j = 0; j < LEAD6; j++) {
                mbar_expect_tx(bar_full + j * 8, STAGE_BYTES);
                tma_3d(sbase + j * STAGE_BYTES, &maps.wq3, 0, (u0 & 1) * 512 + j * 128, u0 >> 1, bar_full + j * 8);
            }
            t0 = gtime32() + OFF6 + (r * NCL + cl) * PACE_T / 128;
#pragma unroll
            for (int i = LEAD6; i < NST; i++) mbar_init(bar_full + i * 8, 1);
#pragma unroll
            for (int i = 0; i < NST; i++) mbar_init(bar_empty + i * 8, 8);
#pragma unroll
            for (int i = 0; i < 5; i++) {
                mbar_init(bar_st + i * 8, 1);
                mbar_expect_tx(bar_st + i * 8, i == 0 ? 384 : 3072);
            }
            *flag = 0u;
            asm volatile("fence.mbarrier_init.release.cluster;" ::: "memory");
            asm volatile("fence.proxy.async.shared::cta;" ::: "memory");
            prefetch_tmap(&maps.w1n);
            prefetch_tmap(&maps.k);
            prefetch_tmap(&maps.v);
            prefetch_tmap(&maps.w2n);
            prefetch_tmap(&maps.won);
        }
        __syncwarp();
        asm volatile("barrier.cluster.arrive.relaxed.aligned;" ::: "memory");
        bar_arrive(BAR_INIT, NTHREADS);
        if (lane == 0) {
            const int kv_row0 = cl * SK + (int)((0x6A56412C1600ull >> (8 * r)) & 0xff) * 64;
            uint32_t fb = bar_full + LEAD6 * 8, eph = 1u;
            uint32_t lb = bar_full + (LEAD6 + NST - CAP6) % NST * 8, lph = 1u;
            uint32_t due = t0 << 8;
#pragma unroll 1
            for (int phase = 0; phase < 7; phase++) {
                const CUtensorMap* map;
                int row, drow = 128, blk, n;
                uint32_t per = (r == 2 || r == 3) ? P_54 : P_52;
                if (phase == 0) {
                    map = &maps.wq3; row = (u0 & 1) * 512 + LEAD6 * 128; blk = u0 >> 1; n = 4 - LEAD6;
                } else if (phase < 3) {
                    const int unit = r < 2 ? u0 + 1 : v0 + phase - 1;
                    map = r < 2 ? &maps.wq3 : &maps.w1n; row = (unit & 1) * 512; blk = unit >> 1;
                    n = (phase == 2 && (r < 2 || r == 5)) ? 0 : 4;
                } else if (phase < 5) {
                    map = phase == 3 ? &maps.k : &maps.v; row = kv_row0; drow = 64; blk = 0; n = nblk;
                } else {
                    map = phase == 5 ? &maps.w2n : &maps.won; row = (phase == 5 ? w2_0 : wo_0) * 128; blk = cl;
                    n = phase == 5 ? n2 : 10 - n2; per = P_B;
                }
#pragma unroll 1
                for (int j = 0; j < n; j++) {
                    const uint32_t dst = sbase + (fb - bar_full) * (STAGE_BYTES / 8);
                    mbar_wait(lb, lph, flag);
                    mbar_wait(fb + NST * 8, eph, flag);
                    mbar_expect_tx(fb, STAGE_BYTES);
                    for (int it = 0; it < 100000 && (int)((gtime32() << 8) - due) < 0; it++) {}
                    tma_3d(dst, map, 0, row, blk, fb);
                    row += drow;
                    due += per;
                    fb += 8;
                    if (fb == bar_empty) { fb = bar_full; eph ^= 1u; }
                    lb += 8;
                    if (lb == bar_empty) { lb = bar_full; lph ^= 1u; }
                }
            }
            KTW(8, 13);
        }
        return;
    }
    asm volatile("barrier.cluster.arrive.relaxed.aligned;" ::: "memory");

    const int g = lane >> 2;
    const int t = lane & 3;
    const int mt = warp & 3;
    const int kh2 = warp >> 2;
    const uint32_t epoch = ld1(scr + G_EPOCH + c * 4) + 1u;
    asm volatile("prefetch.global.L2 [%0];" ::"l"(wq + (size_t)((u0 & 1) * 512 + (tid < 256 ? tid : tid - 32)) * 4096 + (u0 >> 1) * 64));
    const uint32_t tag = 1u + epoch % 3u;

    if (warp >= 9) {
        const int hb = warp - 9;
        const bool fin = r < 4 && hb < 2;
        const int col = cl * 64 + r * 16 + hb * 8 + (lane & 7);
        float b2v = 0.f;
        {
            uint4 xv[4], gw[4];
#pragma unroll
            for (int i = 0; i < 4; i++) xv[i] = __ldg(reinterpret_cast<const uint4*>(x) + hb * 128 + i * 32 + lane);
#pragma unroll
            for (int i = 0; i < 4; i++) gw[i] = __ldg(reinterpret_cast<const uint4*>(gate_w) + i * 32 + lane);
            if (fin) b2v = __bfloat162float(b2[col]);
            bar_sync(BAR_INIT, NTHREADS);
            float s0 = 0.f, s1 = 0.f, zs = 0.f;
#pragma unroll
            for (int i = 0; i < 4; i++) {
                const uint32_t xa[4] = {xv[i].x, xv[i].y, xv[i].z, xv[i].w};
                const uint32_t wa[4] = {gw[i].x, gw[i].y, gw[i].z, gw[i].w};
#pragma unroll
                for (int e = 0; e < 4; e++) {
                    s0 += bf_lo(xa[e]);
                    s1 += bf_hi(xa[e]);
                    zs += bf16r(bf_lo(xa[e]) * bf_lo(wa[e]));
                    zs += bf16r(bf_hi(xa[e]) * bf_hi(wa[e]));
                }
            }
            float s = s0 + s1;
#pragma unroll
            for (int o = 16; o > 0; o >>= 1) {
                s += __shfl_xor_sync(0xffffffffu, s, o);
                zs += __shfl_xor_sync(0xffffffffu, zs, o);
            }
            if (r >= 2) {
                const float mean = s * (1.0f / 1024.0f);
                float q0 = 0.f, q1 = 0.f;
#pragma unroll
                for (int i = 0; i < 4; i++) {
                    const uint32_t xa[4] = {xv[i].x, xv[i].y, xv[i].z, xv[i].w};
#pragma unroll
                    for (int e = 0; e < 4; e++) {
                        const float d0 = bf_lo(xa[e]) - mean, d1 = bf_hi(xa[e]) - mean;
                        q0 = fmaf(d0, d0, q0);
                        q1 = fmaf(d1, d1, q1);
                    }
                }
                float q = q0 + q1;
#pragma unroll
                for (int o = 16; o > 0; o >>= 1) q += __shfl_xor_sync(0xffffffffu, q, o);
                const float mb = bf16r(mean);
                const float vb = bf16r(q * (1.0f / 1024.0f));
                const float den = bf16r(sqrtf(bf16r(vb + 1e-5f)));
#pragma unroll
                for (int i = 0; i < 4; i++) {
                    const uint32_t xa[4] = {xv[i].x, xv[i].y, xv[i].z, xv[i].w};
                    uint32_t ya[4];
#pragma unroll
                    for (int e = 0; e < 4; e++) ya[e] = pack_bf16(bf16r(bf_lo(xa[e]) - mb) / den, bf16r(bf_hi(xa[e]) - mb) / den);
                    *reinterpret_cast<uint4*>(sptr + SM_YS + hb * XS_STRIDE + (i * 32 + lane) * 16) = make_uint4(ya[0], ya[1], ya[2], ya[3]);
                }
                bar_arrive(BAR_Y, 384);
            }
            zs = bf16r(zs);
            if (lane == 0) reinterpret_cast<float*>(sptr + SM_G)[hb] = bf16r(1.0f / (1.0f + __expf(-zs)));
        }
        const int sl = r + 6 * (hb - 2);
        const bool red_o = hb >= 2 && sl < 8;
        unsigned int* const o_dst = scr + G_O + cl * 1024 + g * 128 + sl * 16 + t * 4;
        bar_sync(BAR_HELP, 160);
        if (red_o) st4(o_dst, 0u, 0u, 0u, 0u);
        if (hb == 3) {
            mbar_wait_cluster(bar_st, flag);
            float4 d = make_float4(-INFINITY, 0.f, -INFINITY, 0.f);
            if (g < CS) d = *reinterpret_cast<const float4*>(sptr + SM_ST + lane * 16);
            float M0 = d.x, M1 = d.z;
#pragma unroll
            for (int o = 4; o < 32; o <<= 1) {
                M0 = fmaxf(M0, __shfl_xor_sync(0xffffffffu, M0, o));
                M1 = fmaxf(M1, __shfl_xor_sync(0xffffffffu, M1, o));
            }
            const float w0 = exp2f((d.x - M0) * 1.4426950408889634f), w1 = exp2f((d.z - M1) * 1.4426950408889634f);
            float L0 = w0 * d.y, L1 = w1 * d.w;
#pragma unroll
            for (int o = 4; o < 32; o <<= 1) {
                L0 += __shfl_xor_sync(0xffffffffu, L0, o);
                L1 += __shfl_xor_sync(0xffffffffu, L1, o);
            }
            if (g == r) *reinterpret_cast<float2*>(sptr + SM_F + t * 8) = make_float2(w0 / L0, w1 / L1);
            bar_arrive(BAR_F, 288);
        }
        {
            const unsigned int* p = scr + G_H + hb * 4096 + w2_0 * 128 + lane * 4;
            const uint32_t* pb = reinterpret_cast<const uint32_t*>(b1 + w2_0 * 128 + g * 16 + 2 * t);
#pragma unroll 1
            for (int i = 0; i < n2; i++) {
                const uint32_t ba = __ldg(pb + i * 64), bb = __ldg(pb + i * 64 + 4);
                uint4 d0, d1;
                for (uint32_t it = 0; it < POLL_LIMIT; it++) {
                    d0 = ld4(p + i * 128);
                    d1 = ld4(p + i * 128 + 4 * 4096);
                    if (warp_ok(bad4(d0, tag) | bad4(d1, tag))) break;
                    __nanosleep(200);
                }
                const float sv[4] = {dec(d0.x) + dec(d1.x), dec(d0.z) + dec(d1.z), dec(d0.y) + dec(d1.y), dec(d0.w) + dec(d1.w)};
                const float bv[4] = {bf_lo(ba), bf_hi(ba), bf_lo(bb), bf_hi(bb)};
                float h[4];
#pragma unroll
                for (int e = 0; e < 4; e++) {
                    const float v = bf16r(bf16r(sv[e]) + bv[e]);
                    const float inner = 0.7978845608028654f * (v + 0.044715f * v * v * v);
                    h[e] = 0.5f * v * (1.0f + tanhf(inner));
                }
                sts64(sbase + SM_HS + hb * HS_STRIDE + i * 256 + lane * 8, pack_bf16(h[0], h[1]), pack_bf16(h[2], h[3]));
            }
            KTW(9, 7);
            bar_arrive(BAR_HS, 384);
        }
        const float gate = reinterpret_cast<const float*>(sptr + SM_G)[lane >> 3];
        bar_sync(BAR_O, 384);
        if (red_o) {
            const float4* po = reinterpret_cast<const float4*>(sptr + SM_OR + (hb - 2) * 3072) + lane;
            mbar_wait_cluster(bar_or + (hb - 2) * 8, flag);
            float4 v[CS];
#pragma unroll
            for (int s = 0; s < CS; s++) v[s] = po[s * 32];
            const float o0 = ((v[0].x + v[1].x) + (v[2].x + v[3].x)) + (v[4].x + v[5].x);
            const float o1 = ((v[0].y + v[1].y) + (v[2].y + v[3].y)) + (v[4].y + v[5].y);
            const float o2 = ((v[0].z + v[1].z) + (v[2].z + v[3].z)) + (v[4].z + v[5].z);
            const float o3 = ((v[0].w + v[1].w) + (v[2].w + v[3].w)) + (v[4].w + v[5].w);
            st4(o_dst, __float_as_uint(bf16r(o0)) | tag, __float_as_uint(bf16r(o1)) | tag, __float_as_uint(bf16r(o2)) | tag,
                __float_as_uint(bf16r(o3)) | tag);
            KTW(11, 28);
        }
        __nanosleep(OG6_DELAY);
        {
            const unsigned int* po = scr + G_O + hb * 4096 + wo_0 * 128 + lane * 4;
            uint4 d[6];
            uint32_t pend = r < 4 ? 0x1fu : 0x3fu;
            for (uint32_t it = 0; it < POLL_LIMIT; it++) {
#pragma unroll
                for (int s = 0; s < 6; s++)
                    if (pend & (1u << s)) d[s] = ld4(po + s * 128);
#pragma unroll
                for (int s = 0; s < 6; s++) {
                    if ((pend & (1u << s)) && warp_ok(bad4(d[s], tag))) {
                        pend &= ~(1u << s);
                        sts64(sbase + SM_OS + hb * OS_STRIDE + s * 256 + lane * 8, __byte_perm(d[s].x, d[s].z, 0x7632),
                              __byte_perm(d[s].y, d[s].w, 0x7632));
                    }
                }
                if (pend == 0u) {
                    break;
                }
                __nanosleep(OG_GAP);
            }
            KTA(15);
            bar_arrive(BAR_OS, 384);
        }
        if (fin) {
            const float gm = bf16r(1.0f - gate);
            float term[2];
#pragma unroll
            for (int br = 0; br < 2; br++) {
                const float* xr = reinterpret_cast<const float*>(sptr + SM_XR) + br * 768 + hb * 32 + (lane & 7) * 4 + (lane >> 3);
                mbar_wait_cluster(bar_xr + br * 8, flag);
                KTW(9, 10 + br);
                float v[12];
#pragma unroll
                for (int s = 0; s < 12; s++) v[s] = xr[s * 64];
#pragma unroll
                for (int s = 0; s < 6; s++) v[s] += v[s + 6];
                const float sum = bf16r(((v[0] + v[1]) + (v[2] + v[3])) + (v[4] + v[5]));
                term[br] = br == 0 ? bf16r(gm * bf16r(sum + b2v)) : bf16r(gate * sum);
            }
            out[(lane >> 3) * D_MODEL + col] = __float2bfloat16_rn(term[1] + term[0]);
        }
        KTW(9, 12);
        return;
    }

    {
        const uint4 x0 = __ldg(reinterpret_cast<const uint4*>(x) + tid);
        const uint4 x1 = __ldg(reinterpret_cast<const uint4*>(x) + 256 + tid);
        if (t < 2 && (kh2 == 0 || r < 2)) {
            unsigned int* const q_dst = scr + G_Q + (((u0 + kh2) & 1) * 4 + 2 * t) * 4096 + (u0 >> 1) * 64 + mt * 16 + 2 * g;
            st2(q_dst, 0u, 0u);
            st2(q_dst + 4096, 0u, 0u);
        }
        *reinterpret_cast<uint4*>(sptr + SM_XS + (tid >> 7) * XS_STRIDE + (tid & 127) * 16) = x0;
        *reinterpret_cast<uint4*>(sptr + SM_XS + (2 + (tid >> 7)) * XS_STRIDE + (tid & 127) * 16) = x1;
    }
    bar_sync(BAR_INIT, NTHREADS);

    int stage = 0;
    uint32_t ph = 0;
    const uint32_t l8 = lane & 7;
    const uint32_t rowT = (l8 + 8 * (lane >> 4)) * 128;
    const uint32_t offT = rowT + ((((uint32_t)(2 * mt + ((lane >> 3) & 1))) ^ l8) << 4);
    const uint32_t aoff = sbase + kh2 * 8192 + offT;
    const bool bvalid = g < 4;

#pragma unroll 1
    for (int ui = 0; ui < ((r >= 2 && r <= 4) ? 3 : 2); ui++) {
        const bool isq = ui == 0 || r < 2;
        const int unit = isq ? u0 + ui : v0 + ui - 1;
        float4* const red = reinterpret_cast<float4*>(sptr + SM_RED) + (ui & 1) * 64 + mt * 16 + (g * 2 + (t & 1));
        unsigned int* const dst = scr + (isq ? G_Q : G_H) + ((unit & 1) * 4 + 2 * t) * 4096 + (unit >> 1) * 64 + mt * 16 + 2 * g;
        float acc0[4] = {0.f, 0.f, 0.f, 0.f}, acc1[4] = {0.f, 0.f, 0.f, 0.f};
        const uint32_t baddr = sbase + (isq ? SM_XS : SM_YS) + (g & 3) * XS_STRIDE + ((unit & 1) * 512 + kh2 * 64 + 2 * t) * 2;
        if (ui == 1 && r >= 2) bar_sync(BAR_Y, 384);
#pragma unroll 1
        for (int j = 0; j < 4; j++) {
            mbar_wait(bar_full + stage * 8, ph, flag);
            gemv_tile4(acc0, acc1, aoff + stage * STAGE_BYTES, baddr + j * 256, bvalid);
            __syncwarp();
            if (lane == 0) mbar_arrive_cnt(bar_empty + stage * 8, 1);
            if (++stage == NST) { stage = 0; ph ^= 1u; }
        }
        if (kh2 == 1 && t < 2) *red = make_float4(acc0[0] + acc1[0], acc0[1] + acc1[1], acc0[2] + acc1[2], acc0[3] + acc1[3]);
        bar_sync(BAR_PAIR + mt, 64);
        if (kh2 == 0 && t < 2) {
            const float4 o = *red;
            st2(dst, enc(acc0[0] + acc1[0] + o.x, tag), enc(acc0[2] + acc1[2] + o.z, tag));
            st2(dst + 4096, enc(acc0[1] + acc1[1] + o.y, tag), enc(acc0[3] + acc1[3] + o.w, tag));
        }
    }
    KTW(0, 1);
    mbar_wait(bar_full + stage * 8, ph, flag);
    uint32_t qf[8][2];
    {
        const unsigned int* p = scr + G_Q + cl * 1024 + tid * 4;
        uint4 d0, d1;
        for (uint32_t it = 0; it < POLL_LIMIT; it++) {
            d0 = ld4(p);
            d1 = ld4(p + 4 * 4096);
            if (warp_ok(bad4(d0, tag) | bad4(d1, tag))) break;
            __nanosleep(200);
        }
        sts64(sbase + SM_QS + warp * FR_STRIDE + lane * 8,
              pack_bf16(dec(d0.x) + dec(d1.x), dec(d0.z) + dec(d1.z)), pack_bf16(dec(d0.y) + dec(d1.y), dec(d0.w) + dec(d1.w)));
        bar_sync(BAR_CONS, 256);
#pragma unroll
        for (int ks = 0; ks < 8; ks++) {
            const uint2 v = lds64(sbase + SM_QS + g * FR_STRIDE + (ks * 4 + t) * 8);
            qf[ks][0] = v.x;
            qf[ks][1] = v.y;
        }
    }
    KTW(0, 2);
    {
        float sc[11][4];
        const bool full = nblk - kh2 >= 21;
        {
            int st = stage + kh2;
            uint32_t php = ph;
            if (st >= NST) { st -= NST; php ^= 1u; }
            const uint32_t krow = mt * 16 + l8 + 8 * ((lane >> 3) & 1);
            const uint32_t khi = lane >> 4;
#pragma unroll
            for (int i = 0; i < 11; i++) {
                if (i < 10 || full) {
                    mbar_wait(bar_full + st * 8, php, flag);
                    const uint32_t base = sbase + st * STAGE_BYTES + krow * 128;
                    float c0[4] = {0.f, 0.f, 0.f, 0.f}, c1[4] = {0.f, 0.f, 0.f, 0.f};
                    uint32_t a[8][4];
#pragma unroll
                    for (int ks = 0; ks < 8; ks++)
                        ldsm_x4(a[ks], base + (ks >> 2) * 8192 + (((uint32_t)((ks & 3) * 2) + khi) ^ l8) * 16);
#pragma unroll
                    for (int ks = 0; ks < 8; ks++) {
                        if (ks & 1) mma16816(c1, a[ks], qf[ks][0], qf[ks][1]);
                        else mma16816(c0, a[ks], qf[ks][0], qf[ks][1]);
                    }
                    __syncwarp();
                    if (lane == 0) mbar_arrive_cnt(bar_empty + st * 8, 2);
#pragma unroll
                    for (int e = 0; e < 4; e++) sc[i][e] = bf16r(bf16r(c0[e] + c1[e]) * 0.08838834764831845f);
                    st += 2;
                    if (st >= NST) { st -= NST; php ^= 1u; }
                } else {
#pragma unroll
                    for (int e = 0; e < 4; e++) sc[i][e] = sc[0][e];
                }
            }
            stage += nblk - NST;
            ph ^= 1u;
            if (stage >= NST) { stage -= NST; ph ^= 1u; }
        }
        KTW(0, 3);
        float m0 = sc[0][0], m1 = sc[0][1];
#pragma unroll
        for (int i = 0; i < 11; i++) {
            m0 = fmaxf(m0, fmaxf(sc[i][0], sc[i][2]));
            m1 = fmaxf(m1, fmaxf(sc[i][1], sc[i][3]));
        }
#pragma unroll
        for (int o = 4; o < 32; o <<= 1) {
            m0 = fmaxf(m0, __shfl_xor_sync(0xffffffffu, m0, o));
            m1 = fmaxf(m1, __shfl_xor_sync(0xffffffffu, m1, o));
        }
        float2* mx = reinterpret_cast<float2*>(sptr + SM_MX);
        if (g == 0) mx[warp * 4 + t] = make_float2(m0, m1);
        bar_sync(BAR_CONS, 256);
#pragma unroll
        for (int w = 0; w < 8; w++) {
            const float2 v = mx[w * 4 + t];
            m0 = fmaxf(m0, v.x);
            m1 = fmaxf(m1, v.y);
        }
        float l0 = 0.f, l1 = 0.f;
#pragma unroll
        for (int i = 0; i < 11; i++) {
            if (i < 10 || full) {
                const float e0 = exp2f((sc[i][0] - m0) * 1.4426950408889634f);
                const float e1 = exp2f((sc[i][1] - m1) * 1.4426950408889634f);
                const float e2 = exp2f((sc[i][2] - m0) * 1.4426950408889634f);
                const float e3 = exp2f((sc[i][3] - m1) * 1.4426950408889634f);
                l0 += e0 + e2;
                l1 += e1 + e3;
                const uint32_t key = (2 * i + kh2) * 64 + mt * 16 + g;
                sts32(sbase + SM_P + key * 16 + t * 4, pack_bf16(e0, e1));
                sts32(sbase + SM_P + (key + 8) * 16 + t * 4, pack_bf16(e2, e3));
            }
        }
#pragma unroll
        for (int o = 4; o < 32; o <<= 1) {
            l0 += __shfl_xor_sync(0xffffffffu, l0, o);
            l1 += __shfl_xor_sync(0xffffffffu, l1, o);
        }
        float2* ls = reinterpret_cast<float2*>(sptr + SM_LS);
        if (g == 0) ls[warp * 4 + t] = make_float2(l0, l1);
        bar_sync(BAR_CONS, 256);
        asm volatile("barrier.cluster.wait.acquire.aligned;" ::: "memory");
        if (warp == 0) {
            l0 = 0.f;
            l1 = 0.f;
#pragma unroll
            for (int w = 0; w < 8; w++) {
                const float2 v = ls[w * 4 + t];
                l0 += v.x;
                l1 += v.y;
            }
            if (g < CS) st_async4(mapa(sbase + SM_ST + r * 64 + t * 16, g), m0, l0, m1, l1, mapa(bar_st, g));
            bar_arrive(BAR_HELP, 160);
        }
    }
    {
        float acc0[4] = {0.f, 0.f, 0.f, 0.f}, acc1[4] = {0.f, 0.f, 0.f, 0.f};
        const uint32_t paddr = sbase + SM_P + lane * 16;
        const uint32_t sel = warp >= CS ? 1u : 0u;
        const uint32_t ro = mapa(sbase + SM_OR + sel * 3072 + r * 512 + t * 128 + g * 8, warp - sel * CS);
        const uint32_t rb = mapa(bar_or + sel * 8, warp - sel * CS);
#pragma unroll 1
        for (int j = 0; j < nblk; j++) {
            uint32_t pb[2][4];
            ldsm_x4_t(pb[0], paddr + j * 1024);
            ldsm_x4_t(pb[1], paddr + j * 1024 + 512);
            mbar_wait(bar_full + stage * 8, ph, flag);
            const uint32_t base = aoff + stage * STAGE_BYTES;
            uint32_t a[4][4];
#pragma unroll
            for (int ks = 0; ks < 4; ks++) ldsm_x4_t(a[ks], base + ks * 2048);
            mma16816(acc0, a[0], pb[0][0], pb[0][1]);
            mma16816(acc1, a[1], pb[0][2], pb[0][3]);
            mma16816(acc0, a[2], pb[1][0], pb[1][1]);
            mma16816(acc1, a[3], pb[1][2], pb[1][3]);
            __syncwarp();
            if (lane == 0) mbar_arrive_cnt(bar_empty + stage * 8, 1);
            if (++stage == NST) { stage = 0; ph ^= 1u; }
            if (j == nblk - 2) {
                bar_sync(BAR_F, 288);
                bar_sync(BAR_HS, 384);
            }
        }
        const float2 f = *reinterpret_cast<const float2*>(sptr + SM_F + t * 8);
        st_async2(ro, (acc0[0] + acc1[0]) * f.x, (acc0[2] + acc1[2]) * f.x, rb);
        st_async2(ro + 64, (acc0[1] + acc1[1]) * f.y, (acc0[3] + acc1[3]) * f.y, rb);
        bar_arrive(BAR_O, 384);
    }
    KTW(0, 4);
    const uint32_t ra = mapa(sbase + SM_XR + (r * 2 + kh2) * 256 + g * 16 + (t & 1) * 8, mt);
    const uint32_t rb = mapa(bar_xr, mt);
    uint32_t baddr = sbase + SM_HS + (g & 3) * HS_STRIDE + t * 8 + kh2 * 128;
#pragma unroll 1
    for (int br = 0; br < 2; br++) {
        float acc[4][4];
#pragma unroll
        for (int m = 0; m < 4; m++) acc[m][0] = acc[m][1] = acc[m][2] = acc[m][3] = 0.f;
        const int n = br == 0 ? n2 : 10 - n2;
#pragma unroll 1
        for (int j = 0; j < n; j++) {
            uint2 b[4];
            load_b(b, baddr + j * 256, bvalid);
            mbar_wait(bar_full + stage * 8, ph, flag);
            uint32_t a[4][4];
#pragma unroll
            for (int ks = 0; ks < 4; ks++) ldsm_x4_t(a[ks], aoff + stage * STAGE_BYTES + ks * 2048);
#pragma unroll
            for (int ks = 0; ks < 4; ks++) mma16816(acc[ks], a[ks], b[ks].x, b[ks].y);
            if (++stage == NST) { stage = 0; ph ^= 1u; }
        }
        if (t < 2) {
            st_async2(ra + br * 3072, (acc[0][0] + acc[1][0]) + (acc[2][0] + acc[3][0]), (acc[0][1] + acc[1][1]) + (acc[2][1] + acc[3][1]), rb + br * 8);
            st_async2(ra + br * 3072 + 128, (acc[0][2] + acc[1][2]) + (acc[2][2] + acc[3][2]), (acc[0][3] + acc[1][3]) + (acc[2][3] + acc[3][3]), rb + br * 8);
        }
        if (br == 0) {
            KTW(0, 5);
            baddr = sbase + SM_OS + (g & 3) * OS_STRIDE + t * 8 + kh2 * 128;
            bar_sync(BAR_OS, 384);
        }
    }
    if (tid == 0) *reinterpret_cast<volatile unsigned int*>(scr + G_EPOCH + c * 4) = epoch;
}

}
typedef CUresult (*EncodeFn)(CUtensorMap*, CUtensorMapDataType, cuuint32_t, void*, const cuuint64_t*, const cuuint64_t*,
                             const cuuint32_t*, const cuuint32_t*, CUtensorMapInterleave, CUtensorMapSwizzle,
                             CUtensorMapL2promotion, CUtensorMapFloatOOBfill);

void make_2d(EncodeFn enc_fn, CUtensorMap* tm, void* base, uint64_t cols, uint64_t rows, uint32_t box_rows) {
    cuuint64_t gd[2] = {cols, rows};
    cuuint64_t gs[1] = {cols * 2};
    cuuint32_t bd[2] = {64, box_rows};
    cuuint32_t es[2] = {1, 1};
    enc_fn(tm, CU_TENSOR_MAP_DATA_TYPE_BFLOAT16, 2, base, gd, gs, bd, es, CU_TENSOR_MAP_INTERLEAVE_NONE,
           CU_TENSOR_MAP_SWIZZLE_128B, CU_TENSOR_MAP_L2_PROMOTION_L2_128B, CU_TENSOR_MAP_FLOAT_OOB_FILL_NONE);
}
void make_3d(EncodeFn enc_fn, CUtensorMap* tm, void* base, uint64_t cols, uint64_t rows, uint32_t box_rows, uint32_t box_blocks) {
    cuuint64_t gd[3] = {64, rows, cols / 64};
    cuuint64_t gs[2] = {cols * 2, 128};
    cuuint32_t bd[3] = {64, box_rows, box_blocks};
    cuuint32_t es[3] = {1, 1, 1};
    enc_fn(tm, CU_TENSOR_MAP_DATA_TYPE_BFLOAT16, 3, base, gd, gs, bd, es, CU_TENSOR_MAP_INTERLEAVE_NONE,
           CU_TENSOR_MAP_SWIZZLE_128B, CU_TENSOR_MAP_L2_PROMOTION_L2_128B, CU_TENSOR_MAP_FLOAT_OOB_FILL_NONE);
}

}

extern "C" void kernel_launch(void* const* d_in, const int* in_sizes, int n_in, void* d_out, int out_size) {
    (void)in_sizes; (void)n_in; (void)out_size;
    static TMaps maps;
    static void* cached[6] = {nullptr, nullptr, nullptr, nullptr, nullptr, nullptr};
    static EncodeFn enc_fn = nullptr;
    static void* scr = nullptr;
    static bool use_c6 = false;
    cudaLaunchConfig_t cfg = {};
    cudaLaunchAttribute at[1];
    cfg.gridDim = dim3(c6::NCTA);
    cfg.blockDim = dim3(c6::NTHREADS);
    cfg.dynamicSmemBytes = c6::SM_ALLOC;
    cfg.stream = cudaStreamPerThread;
    at[0].id = cudaLaunchAttributeClusterDimension;
    at[0].val.clusterDim.x = c6::CS;
    at[0].val.clusterDim.y = 1;
    at[0].val.clusterDim.z = 1;
    cfg.attrs = at;
    cfg.numAttrs = 1;
    if (!enc_fn) {
        void* fn = nullptr;
        cudaDriverEntryPointQueryResult qr;
        cudaGetDriverEntryPoint("cuTensorMapEncodeTiled", &fn, cudaEnableDefault, &qr);
        enc_fn = (EncodeFn)fn;
        cudaFuncSetAttribute(fb::fused_kernel, cudaFuncAttributeMaxDynamicSharedMemorySize, fb::SM_ALLOC);
        cudaFuncSetAttribute(c6::fused_kernel, cudaFuncAttributeMaxDynamicSharedMemorySize, c6::SM_ALLOC);
        int ncl = 0;
        if (cudaOccupancyMaxActiveClusters(&ncl, c6::fused_kernel, &cfg) != cudaSuccess) { ncl = 0; (void)cudaGetLastError(); }
        use_c6 = ncl >= c6::NCL;
        if (use_c6) cudaGetSymbolAddress(&scr, c6::g_scratch);
        else cudaGetSymbolAddress(&scr, fb::g_scratch);
    }
    void* cur[6] = {d_in[3], d_in[6], d_in[1], d_in[2], d_in[8], d_in[4]};
    bool same = true;
    for (int i = 0; i < 6; i++) same = same && (cur[i] == cached[i]);
    if (!same) {
        make_2d(enc_fn, &maps.wq, d_in[3], 4096, 1024, 128);
        make_2d(enc_fn, &maps.w1, d_in[6], F_DIM, 1024, 128);
        make_3d(enc_fn, &maps.k, d_in[1], 128, 16 * SK, 64, 2);
        make_3d(enc_fn, &maps.v, d_in[2], 128, 16 * SK, 64, 2);
        make_3d(enc_fn, &maps.w2, d_in[8], 1024, F_DIM, 16, 4);
        make_3d(enc_fn, &maps.wo, d_in[4], 1024, 4096, 16, 4);
        make_3d(enc_fn, &maps.w2n, d_in[8], 1024, F_DIM, 128, 1);
        make_3d(enc_fn, &maps.wq3, d_in[3], 4096, 1024, 128, 1);
        make_3d(enc_fn, &maps.won, d_in[4], 1024, 4096, 128, 1);
        make_3d(enc_fn, &maps.w1n, d_in[6], F_DIM, 1024, 128, 1);
        for (int i = 0; i < 6; i++) cached[i] = cur[i];
    }
    if (use_c6) {
        cudaLaunchKernelEx(&cfg, c6::fused_kernel, (const __nv_bfloat16*)d_in[3], (const __nv_bfloat16*)d_in[0],
                           (unsigned int*)scr, (__nv_bfloat16*)d_out, (const __nv_bfloat16*)d_in[10],
                           (const __nv_bfloat16*)d_in[7], maps, (const __nv_bfloat16*)d_in[9]);
    } else {
        fb::fused_kernel<<<fb::NCTA, fb::NTHREADS, fb::SM_ALLOC, cudaStreamPerThread>>>(
            (const __nv_bfloat16*)d_in[3], (const __nv_bfloat16*)d_in[0], (unsigned int*)scr, (__nv_bfloat16*)d_out,
            (const __nv_bfloat16*)d_in[10], (const __nv_bfloat16*)d_in[7], maps, (const __nv_bfloat16*)d_in[9]);
    }
}
```

```cpp
#include <cuda_runtime.h>
#include <cuda.h>
#include <cuda_bf16.h>
#include <stdint.h>

namespace {

constexpr int NSTAGE = 12;
constexpr int STAGE_BYTES = 16384;

constexpr int D_MODEL = 1024;
constexpr int F_DIM = 3584;
constexpr int SK = 8192;

constexpr int XS_STRIDE = 1032 * 2;
constexpr int FR_STRIDE = 288;

#define PACE_T 652
#define PACE_LEAD 2
#define PACE_OFF PACE_T
#define PW_J 6
#define PACE_CAP 4
#define FP_GAP 160
#define OG_DELAY 400

constexpr int BAR_INIT = 0;
constexpr int BAR_CONS = 1;
constexpr int BAR_PAIR = 2;
constexpr int BAR_X = 6;
constexpr int BAR_ML = 7;
constexpr int BAR_O = 8;
constexpr int BAR_OS = 9;
constexpr int BAR_W1 = 10;
constexpr int BAR_HS = 11;
constexpr int BAR_A = 12;
constexpr int BAR_B = 13;
constexpr int BAR_F = 14;

struct TMaps {
    CUtensorMap wq, w1, k, v, w2, wo, w2n, w1n, wq3, won;
};

__device__ __forceinline__ uint32_t smem_u32(const void* p) { return (uint32_t)__cvta_generic_to_shared(p); }
__device__ __forceinline__ uint32_t gtime32() { uint32_t t; asm volatile("mov.u32 %0, %globaltimer_lo;" : "=r"(t)); return t; }

__device__ __forceinline__ void mbar_init(uint32_t bar, uint32_t cnt) {
    asm volatile("mbarrier.init.shared::cta.b64 [%0], %1;" ::"r"(bar), "r"(cnt) : "memory");
}
__device__ __forceinline__ void mbar_expect_tx(uint32_t bar, uint32_t bytes) {
    asm volatile("mbarrier.arrive.expect_tx.shared::cta.b64 _, [%0], %1;" ::"r"(bar), "r"(bytes) : "memory");
}
__device__ __forceinline__ void mbar_arrive_cnt(uint32_t bar, uint32_t cnt) {
    asm volatile("mbarrier.arrive.shared::cta.b64 _, [%0], %1;" ::"r"(bar), "r"(cnt) : "memory");
}
__device__ __forceinline__ bool mbar_try(uint32_t bar, uint32_t parity) {
    uint32_t ok;
    asm volatile(
        "{\n.reg .pred p;\n"
        "mbarrier.try_wait.parity.shared::cta.b64 p, [%1], %2;\n"
        "selp.u32 %0, 1, 0, p;\n}\n"
        : "=r"(ok)
        : "r"(bar), "r"(parity)
        : "memory");
    return ok != 0;
}
__device__ __noinline__ void mbar_wait_slow(uint32_t bar, uint32_t parity, volatile uint32_t* flag) {
    long long t0 = clock64();
    for (uint32_t it = 0; it < 0x40000000u; it++) {
        if (mbar_try(bar, parity)) return;
        if ((it & 63u) == 63u) {
            if (*flag) return;
            if (clock64() - t0 > 2000000000LL) { *flag = 1u; return; }
        }
    }
}
__device__ __forceinline__ void mbar_wait(uint32_t bar, uint32_t parity, volatile uint32_t* flag) {
    if (mbar_try(bar, parity)) return;
    if (mbar_try(bar, parity)) return;
    mbar_wait_slow(bar, parity, flag);
}

__device__ __forceinline__ void mbar_wait_cluster(uint32_t bar, volatile uint32_t* flag) {
    const long long t0 = clock64();
    for (uint32_t it = 0; it < 0x40000000u; it++) {
        uint32_t ok;
        asm volatile(
            "{\n.reg .pred p;\n"
            "mbarrier.try_wait.parity.acquire.cluster.shared::cta.b64 p, [%1], 0;\n"
            "selp.u32 %0, 1, 0, p;\n}\n"
            : "=r"(ok)
            : "r"(bar)
            : "memory");
        if (ok) return;
        if ((it & 63u) == 63u && (*flag || clock64() - t0 > 4000000000LL)) return;
    }
}

__device__ __forceinline__ void tma_2d(uint32_t dst, const CUtensorMap* tm, int c0, int c1, uint32_t bar) {
    asm volatile(
        "cp.async.bulk.tensor.2d.shared::cluster.global.mbarrier::complete_tx::bytes.L2::cache_hint [%0], [%1, {%3, %4}], [%2], %5;"
        ::"r"(dst), "l"(tm), "r"(bar), "r"(c0), "r"(c1), "l"(0x12F0000000000000ull)
        : "memory");
}
__device__ __forceinline__ void tma_3d(uint32_t dst, const CUtensorMap* tm, int c0, int c1, int c2, uint32_t bar) {
    asm volatile(
        "cp.async.bulk.tensor.3d.shared::cluster.global.mbarrier::complete_tx::bytes.L2::cache_hint [%0], [%1, {%3, %4, %5}], [%2], %6;"
        ::"r"(dst), "l"(tm), "r"(bar), "r"(c0), "r"(c1), "r"(c2), "l"(0x12F0000000000000ull)
        : "memory");
}
__device__ __forceinline__ void bulk_load(uint32_t dst, const void* src, uint32_t bytes, uint32_t bar) {
    asm volatile("cp.async.bulk.shared::cluster.global.mbarrier::complete_tx::bytes [%0], [%1], %2, [%3];"
                 ::"r"(dst), "l"(src), "r"(bytes), "r"(bar)
                 : "memory");
}
__device__ __forceinline__ void prefetch_tmap(const CUtensorMap* tm) {
    asm volatile("prefetch.tensormap [%0];" ::"l"(tm) : "memory");
}
__device__ __forceinline__ void bar_sync(int id, int cnt) { asm volatile("bar.sync %0, %1;" ::"r"(id), "r"(cnt) : "memory"); }
__device__ __forceinline__ void bar_arrive(int id, int cnt) { asm volatile("bar.arrive %0, %1;" ::"r"(id), "r"(cnt) : "memory"); }

__device__ __forceinline__ void ldsm_x4(uint32_t (&r)[4], uint32_t addr) {
    asm volatile("ldmatrix.sync.aligned.m8n8.x4.shared.b16 {%0,%1,%2,%3}, [%4];"
                 : "=r"(r[0]), "=r"(r[1]), "=r"(r[2]), "=r"(r[3])
                 : "r"(addr)
                 : "memory");
}
__device__ __forceinline__ void ldsm_x4_t(uint32_t (&r)[4], uint32_t addr) {
    asm volatile("ldmatrix.sync.aligned.m8n8.x4.trans.shared.b16 {%0,%1,%2,%3}, [%4];"
                 : "=r"(r[0]), "=r"(r[1]), "=r"(r[2]), "=r"(r[3])
                 : "r"(addr)
                 : "memory");
}
__device__ __forceinline__ void mma16816(float (&c)[4], const uint32_t (&a)[4], uint32_t b0, uint32_t b1) {
    asm volatile(
        "mma.sync.aligned.m16n8k16.row.col.f32.bf16.bf16.f32 {%0,%1,%2,%3}, {%4,%5,%6,%7}, {%8,%9}, {%0,%1,%2,%3};"
        : "+f"(c[0]), "+f"(c[1]), "+f"(c[2]), "+f"(c[3])
        : "r"(a[0]), "r"(a[1]), "r"(a[2]), "r"(a[3]), "r"(b0), "r"(b1));
}
__device__ __forceinline__ uint32_t lds32(uint32_t addr) {
    uint32_t v;
    asm volatile("ld.shared.b32 %0, [%1];" : "=r"(v) : "r"(addr) : "memory");
    return v;
}
__device__ __forceinline__ uint2 lds64(uint32_t addr) {
    uint2 v;
    asm volatile("ld.shared.v2.b32 {%0, %1}, [%2];" : "=r"(v.x), "=r"(v.y) : "r"(addr) : "memory");
    return v;
}
__device__ __forceinline__ void sts32(uint32_t addr, uint32_t v) {
    asm volatile("st.shared.b32 [%0], %1;" ::"r"(addr), "r"(v) : "memory");
}
__device__ __forceinline__ void sts64(uint32_t addr, uint32_t a, uint32_t b) {
    asm volatile("st.shared.v2.b32 [%0], {%1, %2};" ::"r"(addr), "r"(a), "r"(b) : "memory");
}

__device__ __forceinline__ float bf16r(float x) { return __bfloat162float(__float2bfloat16_rn(x)); }
__device__ __forceinline__ uint32_t pack_bf16(float lo, float hi) {
    __nv_bfloat162 v = __floats2bfloat162_rn(lo, hi);
    return *reinterpret_cast<uint32_t*>(&v);
}
__device__ __forceinline__ float bf_lo(uint32_t u) { return __uint_as_float(u << 16); }
__device__ __forceinline__ float bf_hi(uint32_t u) { return __uint_as_float(u & 0xffff0000u); }

__device__ __forceinline__ uint32_t enc(float v, uint32_t tag) { return (__float_as_uint(v) & ~3u) | tag; }
__device__ __forceinline__ float dec(uint32_t u) { return __uint_as_float(u & ~3u); }
__device__ __forceinline__ void st2(unsigned int* p, uint32_t a, uint32_t b) {
    asm volatile("st.relaxed.gpu.global.v2.b32 [%0], {%1, %2};" ::"l"(p), "r"(a), "r"(b) : "memory");
}
__device__ __forceinline__ void st4(unsigned int* p, uint32_t a, uint32_t b, uint32_t c, uint32_t d) {
    asm volatile("st.relaxed.gpu.global.v4.b32 [%0], {%1, %2, %3, %4};" ::"l"(p), "r"(a), "r"(b), "r"(c), "r"(d) : "memory");
}
__device__ __forceinline__ uint32_t ld1(const unsigned int* p) {
    uint32_t v;
    asm volatile("ld.relaxed.gpu.global.b32 %0, [%1];" : "=r"(v) : "l"(p) : "memory");
    return v;
}
__device__ __forceinline__ uint2 ld2(const unsigned int* p) {
    uint2 v;
    asm volatile("ld.relaxed.gpu.global.v2.b32 {%0, %1}, [%2];" : "=r"(v.x), "=r"(v.y) : "l"(p) : "memory");
    return v;
}
__device__ __forceinline__ uint4 ld4(const unsigned int* p) {
    uint4 v;
    asm volatile("ld.relaxed.gpu.global.v4.b32 {%0, %1, %2, %3}, [%4];" : "=r"(v.x), "=r"(v.y), "=r"(v.z), "=r"(v.w) : "l"(p) : "memory");
    return v;
}
__device__ __forceinline__ uint32_t bad4(const uint4& v, uint32_t tag) { return (v.x ^ tag) | (v.y ^ tag) | (v.z ^ tag) | (v.w ^ tag); }
__device__ __forceinline__ bool warp_ok(uint32_t bad) { return __all_sync(0xffffffffu, (bad & 3u) == 0u); }
__device__ __forceinline__ void spin_cycles(int n) {
    const uint32_t t0 = (uint32_t)clock64();
    for (int it = 0; it < 1000 && (int)((uint32_t)clock64() - t0) < n; it++) {}
}
constexpr uint32_t POLL_LIMIT = 1u << 21;

__device__ __forceinline__ void gemv_tile4(float (&acc0)[4], float (&acc1)[4], uint32_t a_addr, uint32_t b_addr, bool bvalid) {
    uint32_t a[4][4];
    uint32_t b[4][2];
#pragma unroll
    for (int ks = 0; ks < 4; ks++) ldsm_x4_t(a[ks], a_addr + ks * 2048);
#pragma unroll
    for (int ks = 0; ks < 4; ks++) {
        b[ks][0] = bvalid ? lds32(b_addr + ks * 32) : 0u;
        b[ks][1] = bvalid ? lds32(b_addr + ks * 32 + 16) : 0u;
    }
#pragma unroll
    for (int ks = 0; ks < 4; ks++) {
        if (ks & 1) mma16816(acc1, a[ks], b[ks][0], b[ks][1]);
        else mma16816(acc0, a[ks], b[ks][0], b[ks][1]);
    }
}

template <int N>
__device__ __forceinline__ float final_sum(const unsigned int* buf, int lane, uint32_t tag, bool backoff) {
    const unsigned int* p = buf + (lane >> 3) * (N * 32) + (lane & 7) * 4;
    uint4 d[N];
    for (uint32_t it = 0; it < POLL_LIMIT; it++) {
        uint32_t bad = 0;
#pragma unroll
        for (int i = 0; i < N; i++) { d[i] = ld4(p + i * 32); bad |= bad4(d[i], tag); }
        if (warp_ok(bad)) break;
        if (backoff) __nanosleep(100);
    }
    float s0 = 0.f, s1 = 0.f, s2 = 0.f, s3 = 0.f;
#pragma unroll
    for (int i = 0; i < N; i++) { s0 += dec(d[i].x); s1 += dec(d[i].y); s2 += dec(d[i].z); s3 += dec(d[i].w); }
    const bool hi = lane & 16;
    float u0 = hi ? s0 : s2, u1 = hi ? s1 : s3;
    float k0 = hi ? s2 : s0, k1 = hi ? s3 : s1;
    k0 += __shfl_xor_sync(0xffffffffu, u0, 16);
    k1 += __shfl_xor_sync(0xffffffffu, u1, 16);
    const bool od = lane & 8;
    const float w = od ? k0 : k1;
    float r = od ? k1 : k0;
    r += __shfl_xor_sync(0xffffffffu, w, 8);
    return r;
}

namespace fb {

constexpr int NCTA = 128;
constexpr int NTHREADS = 416;

constexpr int SM_P = NSTAGE * STAGE_BYTES;
constexpr int SM_XS = SM_P;
constexpr int SM_YS = SM_P + 16384;
constexpr int SM_QS = SM_YS + 4160;
constexpr int SM_OS = SM_QS + 2304;
constexpr int SM_HS = SM_OS + 1152;
constexpr int SM_RED = SM_HS + 960;
constexpr int SM_MX = SM_RED + 2048;
constexpr int SM_LS = SM_MX + 256;
constexpr int SM_F = SM_LS + 256;
constexpr int SM_BAR = SM_F + 32;
constexpr int SM_FLAG = SM_BAR + 2 * NSTAGE * 8;
constexpr int SM_TOTAL = SM_FLAG + 8;
constexpr int SM_ALLOC = SM_TOTAL + 1024;

constexpr int YS_STRIDE = 520 * 2;
constexpr int HS_STRIDE = 240;

constexpr int G_EPOCH = 0;
constexpr int G_Q = G_EPOCH + NCTA * 4;
constexpr int G_H = G_Q + 2 * 4 * 4096;
constexpr int G_ML = G_H + 2 * F_DIM * 4;
constexpr int G_O = G_ML + NCTA * 16;
constexpr int G_A = G_O + NCTA * 1024;
constexpr int G_B = G_A + NCTA * 1024;
constexpr int G_TOTAL = G_B + NCTA * 1024;
__device__ __align__(1024) unsigned int g_scratch[G_TOTAL];

__global__ void __launch_bounds__(NTHREADS, 1)
fused_kernel(const __nv_bfloat16* __restrict__ wq, const __nv_bfloat16* __restrict__ x, unsigned int* __restrict__ scr,
             __nv_bfloat16* __restrict__ out, const __nv_bfloat16* __restrict__ gate_w, const __nv_bfloat16* __restrict__ b1,
             const __grid_constant__ TMaps maps, const __nv_bfloat16* __restrict__ b2) {
    extern __shared__ unsigned char smem_raw[];
    const uint32_t sbase = (smem_u32(smem_raw) + 1023u) & ~1023u;
    unsigned char* sptr = smem_raw + (sbase - smem_u32(smem_raw));
    volatile uint32_t* flag = reinterpret_cast<volatile uint32_t*>(sptr + SM_FLAG);

    const int c = blockIdx.x;
    const int tid = threadIdx.x;
    const int warp = tid >> 5;
    const int lane = tid & 31;
    const bool has_w1 = c < 112;
    const int kb = c >> 2, nb = c & 3;
    const uint32_t bar_full = sbase + SM_BAR;
    const uint32_t bar_empty = sbase + SM_BAR + NSTAGE * 8;

    if (warp == 8) {
        const int n_w1 = has_w1 ? 4 : 0;
        const int n_tiles = 44 + n_w1;
        const int kv_row0 = (c >> 3) * SK + (c & 7) * 1024;
        uint32_t due = 0;
        if (lane == 0) {
#pragma unroll
            for (int j = 0; j < PACE_LEAD; j++) mbar_init(bar_full + j * 8, 1);
            asm volatile("fence.mbarrier_init.release.cluster;" ::: "memory");
            asm volatile("fence.proxy.async.shared::cta;" ::: "memory");
#pragma unroll
            for (int j = 0; j < PACE_LEAD; j++) {
                mbar_expect_tx(bar_full + j * 8, STAGE_BYTES);
                tma_2d(sbase + j * STAGE_BYTES, &maps.wq, (c >> 1) * 64, (c & 1) * 512 + j * 128, bar_full + j * 8);
            }
            due = gtime32() + PACE_OFF + (c >> 1) * PACE_T / 64;
#pragma unroll
            for (int i = PACE_LEAD; i < NSTAGE; i++) mbar_init(bar_full + i * 8, 1);
#pragma unroll
            for (int i = 0; i < NSTAGE; i++) mbar_init(bar_empty + i * 8, 8);
            *flag = 0u;
            asm volatile("fence.mbarrier_init.release.cluster;" ::: "memory");
            asm volatile("fence.proxy.async.shared::cta;" ::: "memory");
            prefetch_tmap(&maps.w1);
            prefetch_tmap(&maps.k);
            prefetch_tmap(&maps.v);
            prefetch_tmap(&maps.w2);
            prefetch_tmap(&maps.wo);
        }
        __syncwarp();
        bar_arrive(BAR_INIT, NTHREADS);
        if (lane == 0) {
            int landed = 0;
            for (int i = PACE_LEAD; i < n_tiles; i++) {
                while (landed + PACE_CAP <= i) {
                    mbar_wait(bar_full + (landed % NSTAGE) * 8, (uint32_t)(landed / NSTAGE) & 1u, flag);
                    landed++;
                }
                const int stage = i % NSTAGE;
                if (i >= NSTAGE) mbar_wait(bar_empty + stage * 8, (uint32_t)(i / NSTAGE - 1) & 1u, flag);
                for (int it = 0; it < 100000 && (int)(gtime32() - due) < 0; it++) {}
                const uint32_t dst = sbase + stage * STAGE_BYTES;
                const uint32_t fb = bar_full + stage * 8;
                int j = i - 4;
                if (j < 0) {
                    mbar_expect_tx(fb, STAGE_BYTES);
                    tma_2d(dst, &maps.wq, (c >> 1) * 64, (c & 1) * 512 + i * 128, fb);
                    due += (j == -1 && !has_w1) ? PACE_T * 9 / 2 : PACE_T;
                } else if (j < n_w1) {
                    mbar_expect_tx(fb, STAGE_BYTES);
                    tma_2d(dst, &maps.w1, (c >> 1) * 64, (c & 1) * 512 + j * 128, fb);
                    due += PACE_T * 7 / 8;
                } else if (j < 32 + n_w1) {
                    j -= n_w1;
                    mbar_expect_tx(fb, STAGE_BYTES);
                    tma_3d(dst, j < 16 ? &maps.k : &maps.v, 0, kv_row0 + (j & 15) * 64, 0, fb);
                    due += PACE_T;
                } else {
                    j -= 32 + n_w1;
                    const CUtensorMap* tm = j < 4 ? &maps.w2 : &maps.wo;
                    const int row = j < 4 ? kb * 112 + j * 32 : kb * 128 + (j - 4) * 32;
                    mbar_expect_tx(fb, j != 3 ? STAGE_BYTES : STAGE_BYTES / 2);
                    tma_3d(dst, tm, 0, row, nb * 4, fb);
                    if (j != 3) tma_3d(dst + 8192, tm, 0, row + 16, nb * 4, fb);
                    due += j != 3 ? PACE_T : PACE_T / 2;
                }
            }
        }
        return;
    }

    const int g = lane >> 2;
    const int t = lane & 3;
    const int khalf = c & 1;
    const int pair = c >> 3;
    const int mt = warp & 3;
    const int kh2 = warp >> 2;
    const uint32_t epoch = ld1(scr + G_EPOCH + c * 4) + 1u;
    unsigned int* const q_dst = scr + G_Q + (khalf * 4 + 2 * t) * 4096 + (c >> 1) * 64 + mt * 16 + 2 * g;
    unsigned int* const h_dst = scr + G_H + (khalf * F_DIM + (c >> 1) * 64 + mt * 16 + g) * 4 + 2 * t;
    if (warp < 8) {
        asm volatile("prefetch.global.L2 [%0];" ::"l"(wq + (size_t)(khalf * 512 + tid) * 4096 + (c >> 1) * 64));
        const uint4 x0 = __ldg(reinterpret_cast<const uint4*>(x) + tid);
        const uint4 x1 = __ldg(reinterpret_cast<const uint4*>(x) + 256 + tid);
        if (warp < 4 && t < 2) {
            st2(q_dst, 0u, 0u);
            st2(q_dst + 4096, 0u, 0u);
            if (has_w1) {
                st2(h_dst, 0u, 0u);
                st2(h_dst + 32, 0u, 0u);
            }
        }
        *reinterpret_cast<uint4*>(sptr + SM_XS + (tid >> 7) * XS_STRIDE + (tid & 127) * 16) = x0;
        *reinterpret_cast<uint4*>(sptr + SM_XS + (2 + (tid >> 7)) * XS_STRIDE + (tid & 127) * 16) = x1;
    }
    const uint32_t tag = 1u + epoch % 3u;

    if (warp >= 9) {
        float gate = 0.f, b2v = 0.f;
        if (warp == 9) {
            uint4 gw[4];
#pragma unroll
            for (int i = 0; i < 4; i++) gw[i] = __ldg(reinterpret_cast<const uint4*>(gate_w) + i * 32 + lane);
            b2v = __bfloat162float(b2[c * 8 + (lane & 7)]);
            bar_sync(BAR_INIT, NTHREADS);
            float zz = 0.f;
#pragma unroll 1
            for (int b = 0; b < 4; b++) {
                float zs = 0.f;
#pragma unroll
                for (int i = 0; i < 4; i++) {
                    const uint4 xv = *reinterpret_cast<const uint4*>(sptr + SM_XS + b * XS_STRIDE + (i * 32 + lane) * 16);
                    const uint32_t xa[4] = {xv.x, xv.y, xv.z, xv.w};
                    const uint32_t wa[4] = {gw[i].x, gw[i].y, gw[i].z, gw[i].w};
#pragma unroll
                    for (int e = 0; e < 4; e++) {
                        zs += bf16r(bf_lo(xa[e]) * bf_lo(wa[e]));
                        zs += bf16r(bf_hi(xa[e]) * bf_hi(wa[e]));
                    }
                }
#pragma unroll
                for (int o = 16; o > 0; o >>= 1) zs += __shfl_xor_sync(0xffffffffu, zs, o);
                if ((lane >> 3) == b) zz = zs;
            }
            bar_arrive(BAR_X, 288);
            zz = bf16r(zz);
            gate = bf16r(1.0f / (1.0f + __expf(-zz)));
            if (lane == 0) *reinterpret_cast<volatile unsigned int*>(scr + G_EPOCH + c * 4) = epoch;
        } else if (warp == 11) {
            const bool has4 = lane < 16;
            float bias[4];
#pragma unroll
            for (int i = 0; i < 4; i++) bias[i] = (i < 3 || has4) ? __bfloat162float(b1[kb * 112 + i * 32 + lane]) : 0.f;
            bar_sync(BAR_INIT, NTHREADS);
            bar_sync(BAR_W1, 288);
            const unsigned int* p = scr + G_H + (kb * 112 + lane) * 4;
            uint4 d[4][2];
            for (uint32_t it = 0; it < POLL_LIMIT; it++) {
                __nanosleep(1000);
                uint32_t bad = 0;
#pragma unroll
                for (int i = 0; i < 4; i++) {
                    if (i < 3 || has4) {
                        d[i][0] = ld4(p + i * 128);
                        d[i][1] = ld4(p + i * 128 + F_DIM * 4);
                        bad |= bad4(d[i][0], tag) | bad4(d[i][1], tag);
                    }
                }
                if (warp_ok(bad)) break;
            }
#pragma unroll
            for (int i = 0; i < 4; i++) {
                if (i < 3 || has4) {
                    const int cl = i * 32 + lane;
                    const uint32_t u0[4] = {d[i][0].x, d[i][0].y, d[i][0].z, d[i][0].w};
                    const uint32_t u1[4] = {d[i][1].x, d[i][1].y, d[i][1].z, d[i][1].w};
#pragma unroll
                    for (int b = 0; b < 4; b++) {
                        float v = bf16r(dec(u0[b]) + dec(u1[b]));
                        v = bf16r(v + bias[i]);
                        const float inner = 0.7978845608028654f * (v + 0.044715f * v * v * v);
                        const float hv = 0.5f * v * (1.0f + tanhf(inner));
                        *reinterpret_cast<__nv_bfloat16*>(sptr + SM_HS + b * HS_STRIDE + cl * 2) = __float2bfloat16_rn(hv);
                    }
                }
            }
            bar_arrive(BAR_HS, 288);
        } else if (warp == 12) {
            bar_sync(BAR_INIT, NTHREADS);
            bar_sync(BAR_ML, 64);
            const unsigned int* p = scr + G_ML + pair * 128 + lane * 4;
            uint4 d;
            for (uint32_t it = 0; it < POLL_LIMIT; it++) {
                __nanosleep(1000);
                d = ld4(p);
                if (warp_ok(bad4(d, tag))) break;
            }
            const float m0 = dec(d.x), m1 = dec(d.z);
            float M0 = m0, M1 = m1;
#pragma unroll
            for (int o = 4; o < 32; o <<= 1) {
                M0 = fmaxf(M0, __shfl_xor_sync(0xffffffffu, M0, o));
                M1 = fmaxf(M1, __shfl_xor_sync(0xffffffffu, M1, o));
            }
            const float w0 = exp2f((m0 - M0) * 1.4426950408889634f), w1 = exp2f((m1 - M1) * 1.4426950408889634f);
            float L0 = w0 * dec(d.y), L1 = w1 * dec(d.w);
#pragma unroll
            for (int o = 4; o < 32; o <<= 1) {
                L0 += __shfl_xor_sync(0xffffffffu, L0, o);
                L1 += __shfl_xor_sync(0xffffffffu, L1, o);
            }
            if (g == (c & 7)) *reinterpret_cast<float2*>(sptr + SM_F + t * 8) = make_float2(w0 / L0, w1 / L1);
            bar_arrive(BAR_F, 288);
        } else {
            bar_sync(BAR_INIT, NTHREADS);
        }
        {
            const int hb = warp - 9;
            const unsigned int* po = scr + G_O + ((hb * 4 + (kb >> 3)) * 8 + (kb & 7)) * 1024 + lane * 4;
            uint4 d[8];
            uint32_t pend = 0xffu;
            bar_sync(BAR_O, 384);
            __nanosleep(OG_DELAY);
            for (uint32_t it = 0; it < POLL_LIMIT; it++) {
#pragma unroll
                for (int s = 0; s < 8; s++)
                    if (pend & (1u << s)) d[s] = ld4(po + s * 128);
#pragma unroll
                for (int s = 0; s < 8; s++)
                    if ((pend & (1u << s)) && warp_ok(bad4(d[s], tag))) pend &= ~(1u << s);
                if (pend == 0u) break;
                __nanosleep(100);
            }
            float o0 = 0.f, o1 = 0.f, o2 = 0.f, o3 = 0.f;
#pragma unroll
            for (int s = 0; s < 8; s++) {
                o0 += dec(d[s].x);
                o1 += dec(d[s].y);
                o2 += dec(d[s].z);
                o3 += dec(d[s].w);
            }
            sts64(sbase + SM_OS + hb * FR_STRIDE + lane * 8, pack_bf16(o0, o2), pack_bf16(o1, o3));
            bar_arrive(BAR_OS, 384);
        }
        if (warp != 9) return;
        bar_sync(BAR_B, 288);
        const float bv = bf16r(bf16r(final_sum<8>(scr + G_B + c * 1024, lane, tag, true)) + b2v);
        const float bterm = bf16r(bf16r(1.0f - gate) * bv);
        bar_sync(BAR_A, 288);
        const float aterm = bf16r(gate * bf16r(final_sum<8>(scr + G_A + c * 1024, lane, tag, false)));
        out[(lane >> 3) * D_MODEL + c * 8 + (lane & 7)] = __float2bfloat16_rn(aterm + bterm);
        return;
    }

    bar_sync(BAR_INIT, NTHREADS);

    int stage = 0;
    uint32_t ph = 0;
    const uint32_t l8 = lane & 7;
    const uint32_t rowT = (l8 + 8 * (lane >> 4)) * 128;
    const uint32_t offT = rowT + ((((uint32_t)(2 * mt + ((lane >> 3) & 1))) ^ l8) << 4);
    const bool bvalid = g < 4;
    const int dst_off = ((nb * 32 + warp * 4) * 32 + kb) * 32 + g * 4 + 2 * t;

    {
        float acc0[4] = {0.f, 0.f, 0.f, 0.f}, acc1[4] = {0.f, 0.f, 0.f, 0.f};
        const uint32_t baddr = sbase + SM_XS + (g & 3) * XS_STRIDE + (khalf * 512 + kh2 * 64 + 2 * t) * 2;
#pragma unroll 1
        for (int j = 0; j < 4; j++) {
            mbar_wait(bar_full + stage * 8, ph, flag);
            gemv_tile4(acc0, acc1, sbase + stage * STAGE_BYTES + kh2 * 8192 + offT, baddr + j * 256, bvalid);
            __syncwarp();
            if (lane == 0) mbar_arrive_cnt(bar_empty + stage * 8, 1);
            ++stage;
        }
        float4* red = reinterpret_cast<float4*>(sptr + SM_RED) + mt * 16 + (g * 2 + (t & 1));
        if (kh2 == 1 && t < 2) *red = make_float4(acc0[0] + acc1[0], acc0[1] + acc1[1], acc0[2] + acc1[2], acc0[3] + acc1[3]);
        bar_sync(BAR_PAIR + mt, 64);
        if (kh2 == 0 && t < 2) {
            const float4 o = *red;
            st2(q_dst, enc(acc0[0] + acc1[0] + o.x, tag), enc(acc0[2] + acc1[2] + o.z, tag));
            st2(q_dst + 4096, enc(acc0[1] + acc1[1] + o.y, tag), enc(acc0[3] + acc1[3] + o.w, tag));
        }
    }
    if (has_w1) {
        {
            uint4 xv[4];
#pragma unroll
            for (int i = 0; i < 4; i++) xv[i] = *reinterpret_cast<const uint4*>(sptr + SM_XS + mt * XS_STRIDE + (i * 32 + lane) * 16);
            const uint4 xs = *reinterpret_cast<const uint4*>(sptr + SM_XS + mt * XS_STRIDE + (khalf * 64 + kh2 * 32 + lane) * 16);
            float s0 = 0.f, s1 = 0.f;
#pragma unroll
            for (int i = 0; i < 4; i++) {
                const uint32_t xa[4] = {xv[i].x, xv[i].y, xv[i].z, xv[i].w};
#pragma unroll
                for (int e = 0; e < 4; e++) { s0 += bf_lo(xa[e]); s1 += bf_hi(xa[e]); }
            }
            float s = s0 + s1;
#pragma unroll
            for (int o = 16; o > 0; o >>= 1) s += __shfl_xor_sync(0xffffffffu, s, o);
            const float mean = s * (1.0f / 1024.0f);
            float q0 = 0.f, q1 = 0.f;
#pragma unroll
            for (int i = 0; i < 4; i++) {
                const uint32_t xa[4] = {xv[i].x, xv[i].y, xv[i].z, xv[i].w};
#pragma unroll
                for (int e = 0; e < 4; e++) {
                    const float d0 = bf_lo(xa[e]) - mean, d1 = bf_hi(xa[e]) - mean;
                    q0 = fmaf(d0, d0, q0);
                    q1 = fmaf(d1, d1, q1);
                }
            }
            float q = q0 + q1;
#pragma unroll
            for (int o = 16; o > 0; o >>= 1) q += __shfl_xor_sync(0xffffffffu, q, o);
            const float mb = bf16r(mean);
            const float vb = bf16r(q * (1.0f / 1024.0f));
            const float den = bf16r(sqrtf(bf16r(vb + 1e-5f)));
            const uint32_t xa[4] = {xs.x, xs.y, xs.z, xs.w};
            uint32_t ya[4];
#pragma unroll
            for (int e = 0; e < 4; e++) ya[e] = pack_bf16(bf16r(bf_lo(xa[e]) - mb) / den, bf16r(bf_hi(xa[e]) - mb) / den);
            *reinterpret_cast<uint4*>(sptr + SM_YS + mt * YS_STRIDE + (kh2 * 32 + lane) * 16) = make_uint4(ya[0], ya[1], ya[2], ya[3]);
            bar_sync(BAR_CONS, 256);
        }
        float acc0[4] = {0.f, 0.f, 0.f, 0.f}, acc1[4] = {0.f, 0.f, 0.f, 0.f};
        const uint32_t baddr = sbase + SM_YS + (g & 3) * YS_STRIDE + (kh2 * 64 + 2 * t) * 2;
#pragma unroll 1
        for (int j = 0; j < 4; j++) {
            mbar_wait(bar_full + stage * 8, ph, flag);
            gemv_tile4(acc0, acc1, sbase + stage * STAGE_BYTES + kh2 * 8192 + offT, baddr + j * 256, bvalid);
            __syncwarp();
            if (lane == 0) mbar_arrive_cnt(bar_empty + stage * 8, 1);
            ++stage;
        }
        float4* red = reinterpret_cast<float4*>(sptr + SM_RED + 1024) + mt * 16 + (g * 2 + (t & 1));
        if (kh2 == 1 && t < 2) *red = make_float4(acc0[0] + acc1[0], acc0[1] + acc1[1], acc0[2] + acc1[2], acc0[3] + acc1[3]);
        bar_sync(BAR_PAIR + mt, 64);
        if (kh2 == 0 && t < 2) {
            const float4 o = *red;
            st2(h_dst, enc(acc0[0] + acc1[0] + o.x, tag), enc(acc0[1] + acc1[1] + o.y, tag));
            st2(h_dst + 32, enc(acc0[2] + acc1[2] + o.z, tag), enc(acc0[3] + acc1[3] + o.w, tag));
        }
    } else {
        mbar_wait(bar_full + stage * 8, ph, flag);
    }
    bar_arrive(BAR_W1, 288);
    uint32_t qf[8][2];
    {
        const unsigned int* p = scr + G_Q + (pair >> 2) * 4096 + (pair & 3) * 1024 + tid * 4;
        uint4 d0, d1;
        for (uint32_t it = 0; it < POLL_LIMIT; it++) {
            d0 = ld4(p);
            d1 = ld4(p + 4 * 4096);
            if (warp_ok(bad4(d0, tag) | bad4(d1, tag))) break;
            __nanosleep(200);
        }
        sts64(sbase + SM_QS + warp * FR_STRIDE + lane * 8,
              pack_bf16(dec(d0.x) + dec(d1.x), dec(d0.z) + dec(d1.z)), pack_bf16(dec(d0.y) + dec(d1.y), dec(d0.w) + dec(d1.w)));
        bar_sync(BAR_CONS, 256);
#pragma unroll
        for (int ks = 0; ks < 8; ks++) {
            const uint2 v = lds64(sbase + SM_QS + g * FR_STRIDE + (ks * 4 + t) * 8);
            qf[ks][0] = v.x;
            qf[ks][1] = v.y;
        }
    }
    float sc[8][4];
    {
        int st = stage + kh2;
        uint32_t php = ph;
        const uint32_t krow = mt * 16 + l8 + 8 * ((lane >> 3) & 1);
        const uint32_t khi = lane >> 4;
#pragma unroll
        for (int i = 0; i < 8; i++) {
            mbar_wait(bar_full + st * 8, php, flag);
            const uint32_t base = sbase + st * STAGE_BYTES + krow * 128;
            float c0[4] = {0.f, 0.f, 0.f, 0.f}, c1[4] = {0.f, 0.f, 0.f, 0.f};
            uint32_t a[8][4];
#pragma unroll
            for (int ks = 0; ks < 8; ks++)
                ldsm_x4(a[ks], base + (ks >> 2) * 8192 + (((uint32_t)((ks & 3) * 2) + khi) ^ l8) * 16);
#pragma unroll
            for (int ks = 0; ks < 8; ks++) {
                if (ks & 1) mma16816(c1, a[ks], qf[ks][0], qf[ks][1]);
                else mma16816(c0, a[ks], qf[ks][0], qf[ks][1]);
            }
            __syncwarp();
            if (lane == 0) mbar_arrive_cnt(bar_empty + st * 8, 2);
#pragma unroll
            for (int e = 0; e < 4; e++) sc[i][e] = bf16r(bf16r(c0[e] + c1[e]) * 0.08838834764831845f);
            st += 2;
            if (st >= NSTAGE) { st -= NSTAGE; php ^= 1u; }
        }
        stage += 16 - NSTAGE;
        ph ^= 1u;
        if (stage >= NSTAGE) { stage -= NSTAGE; ph ^= 1u; }
    }
    {
        float m0 = sc[0][0], m1 = sc[0][1];
#pragma unroll
        for (int i = 0; i < 8; i++) {
            m0 = fmaxf(m0, fmaxf(sc[i][0], sc[i][2]));
            m1 = fmaxf(m1, fmaxf(sc[i][1], sc[i][3]));
        }
#pragma unroll
        for (int o = 4; o < 32; o <<= 1) {
            m0 = fmaxf(m0, __shfl_xor_sync(0xffffffffu, m0, o));
            m1 = fmaxf(m1, __shfl_xor_sync(0xffffffffu, m1, o));
        }
        float2* mx = reinterpret_cast<float2*>(sptr + SM_MX);
        if (g == 0) mx[warp * 4 + t] = make_float2(m0, m1);
        bar_sync(BAR_X, 288);
#pragma unroll
        for (int w = 0; w < 8; w++) {
            const float2 v = mx[w * 4 + t];
            m0 = fmaxf(m0, v.x);
            m1 = fmaxf(m1, v.y);
        }
        float l0 = 0.f, l1 = 0.f;
#pragma unroll
        for (int i = 0; i < 8; i++) {
            const float e0 = exp2f((sc[i][0] - m0) * 1.4426950408889634f);
            const float e1 = exp2f((sc[i][1] - m1) * 1.4426950408889634f);
            const float e2 = exp2f((sc[i][2] - m0) * 1.4426950408889634f);
            const float e3 = exp2f((sc[i][3] - m1) * 1.4426950408889634f);
            l0 += e0 + e2;
            l1 += e1 + e3;
            const uint32_t key = (2 * i + kh2) * 64 + mt * 16 + g;
            sts32(sbase + SM_P + key * 16 + t * 4, pack_bf16(e0, e1));
            sts32(sbase + SM_P + (key + 8) * 16 + t * 4, pack_bf16(e2, e3));
        }
#pragma unroll
        for (int o = 4; o < 32; o <<= 1) {
            l0 += __shfl_xor_sync(0xffffffffu, l0, o);
            l1 += __shfl_xor_sync(0xffffffffu, l1, o);
        }
        float2* ls = reinterpret_cast<float2*>(sptr + SM_LS);
        if (g == 0) ls[warp * 4 + t] = make_float2(l0, l1);
        bar_sync(BAR_CONS, 256);
        if (warp == 0) {
            l0 = 0.f;
            l1 = 0.f;
#pragma unroll
            for (int w = 0; w < 8; w++) {
                const float2 v = ls[w * 4 + t];
                l0 += v.x;
                l1 += v.y;
            }
            if (g == 0) st4(scr + G_ML + c * 16 + t * 4, enc(m0, tag), enc(l0, tag), enc(m1, tag), enc(l1, tag));
            bar_arrive(BAR_ML, 64);
        }
    }
    {
        float acc0[4] = {0.f, 0.f, 0.f, 0.f}, acc1[4] = {0.f, 0.f, 0.f, 0.f};
        const uint32_t paddr = sbase + SM_P + lane * 16;
        unsigned int* p = scr + G_O + ((pair * 8 + 2 * t) * 8 + (c & 7)) * 128 + warp * 16 + 2 * g;
#pragma unroll 1
        for (int j = 0; j < 16; j++) {
            if (j == PW_J) {
                st2(p, 0u, 0u);
                st2(p + 1024, 0u, 0u);
                if (t < 2) {
#pragma unroll
                    for (int e = 0; e < 4; e++) {
                        st2(scr + G_A + dst_off + e * 1024, 0u, 0u);
                        st2(scr + G_B + dst_off + e * 1024, 0u, 0u);
                    }
                }
            }
            uint32_t pb[2][4];
            ldsm_x4_t(pb[0], paddr + j * 1024);
            ldsm_x4_t(pb[1], paddr + j * 1024 + 512);
            mbar_wait(bar_full + stage * 8, ph, flag);
            const uint32_t base = sbase + stage * STAGE_BYTES + kh2 * 8192 + offT;
            uint32_t a[4][4];
#pragma unroll
            for (int ks = 0; ks < 4; ks++) ldsm_x4_t(a[ks], base + ks * 2048);
            mma16816(acc0, a[0], pb[0][0], pb[0][1]);
            mma16816(acc1, a[1], pb[0][2], pb[0][3]);
            mma16816(acc0, a[2], pb[1][0], pb[1][1]);
            mma16816(acc1, a[3], pb[1][2], pb[1][3]);
            __syncwarp();
            if (lane == 0) mbar_arrive_cnt(bar_empty + stage * 8, 1);
            if (++stage == NSTAGE) { stage = 0; ph ^= 1u; }
            if (j == 14) bar_sync(BAR_F, 288);
        }
        const float2 f = *reinterpret_cast<const float2*>(sptr + SM_F + t * 8);
        st2(p, enc((acc0[0] + acc1[0]) * f.x, tag), enc((acc0[2] + acc1[2]) * f.x, tag));
        st2(p + 1024, enc((acc0[1] + acc1[1]) * f.y, tag), enc((acc0[3] + acc1[3]) * f.y, tag));
        bar_arrive(BAR_O, 384);
    }
    const uint32_t offW0 = (warp >> 1) * 2048 + rowT + ((((uint32_t)(4 * (warp & 1) + ((lane >> 3) & 1))) ^ l8) << 4);
    const uint32_t offW1 = (warp >> 1) * 2048 + rowT + ((((uint32_t)(4 * (warp & 1) + 2 + ((lane >> 3) & 1))) ^ l8) << 4);
    {
        bar_sync(BAR_HS, 288);
        float acc0[4] = {0.f, 0.f, 0.f, 0.f}, acc1[4] = {0.f, 0.f, 0.f, 0.f};
        const uint32_t baddr = sbase + SM_HS + (g & 3) * HS_STRIDE + t * 4;
#pragma unroll 1
        for (int j = 0; j < 3; j++) {
            uint32_t b[4] = {0u, 0u, 0u, 0u};
            if (bvalid) {
#pragma unroll
                for (int e = 0; e < 4; e++) b[e] = lds32(baddr + j * 64 + e * 16);
            }
            mbar_wait(bar_full + stage * 8, ph, flag);
            const uint32_t base = sbase + stage * STAGE_BYTES;
            uint32_t a[4][4];
            ldsm_x4_t(a[0], base + offW0);
            ldsm_x4_t(a[1], base + offW1);
            ldsm_x4_t(a[2], base + 8192 + offW0);
            ldsm_x4_t(a[3], base + 8192 + offW1);
            mma16816(acc0, a[0], b[0], b[1]);
            mma16816(acc1, a[1], b[0], b[1]);
            mma16816(acc0, a[2], b[2], b[3]);
            mma16816(acc1, a[3], b[2], b[3]);
            ++stage;
        }
        {
            uint32_t b0 = 0u, b1_ = 0u;
            if (bvalid) { b0 = lds32(baddr + 192); b1_ = lds32(baddr + 208); }
            mbar_wait(bar_full + stage * 8, ph, flag);
            const uint32_t base = sbase + stage * STAGE_BYTES;
            uint32_t a[2][4];
            ldsm_x4_t(a[0], base + offW0);
            ldsm_x4_t(a[1], base + offW1);
            mma16816(acc0, a[0], b0, b1_);
            mma16816(acc1, a[1], b0, b1_);
            ++stage;
        }
        if (t < 2) {
            unsigned int* p = scr + G_B + dst_off;
            st2(p, enc(acc0[0], tag), enc(acc0[1], tag));
            st2(p + 1024, enc(acc0[2], tag), enc(acc0[3], tag));
            st2(p + 2048, enc(acc1[0], tag), enc(acc1[1], tag));
            st2(p + 3072, enc(acc1[2], tag), enc(acc1[3], tag));
        }
        bar_arrive(BAR_B, 288);
    }
    {
        bar_sync(BAR_OS, 384);
        float acc0[4] = {0.f, 0.f, 0.f, 0.f}, acc1[4] = {0.f, 0.f, 0.f, 0.f};
        const uint32_t baddr = sbase + SM_OS + (g & 3) * FR_STRIDE + t * 8;
#pragma unroll 1
        for (int j = 0; j < 4; j++) {
            uint2 b0 = make_uint2(0u, 0u), b1_ = make_uint2(0u, 0u);
            if (bvalid) { b0 = lds64(baddr + j * 64); b1_ = lds64(baddr + j * 64 + 32); }
            mbar_wait(bar_full + stage * 8, ph, flag);
            const uint32_t base = sbase + stage * STAGE_BYTES;
            uint32_t a[4][4];
            ldsm_x4_t(a[0], base + offW0);
            ldsm_x4_t(a[1], base + offW1);
            ldsm_x4_t(a[2], base + 8192 + offW0);
            ldsm_x4_t(a[3], base + 8192 + offW1);
            mma16816(acc0, a[0], b0.x, b0.y);
            mma16816(acc1, a[1], b0.x, b0.y);
            mma16816(acc0, a[2], b1_.x, b1_.y);
            mma16816(acc1, a[3], b1_.x, b1_.y);
            ++stage;
        }
        if (t < 2) {
            unsigned int* p = scr + G_A + dst_off;
            st2(p, enc(acc0[0], tag), enc(acc0[1], tag));
            st2(p + 1024, enc(acc0[2], tag), enc(acc0[3], tag));
            st2(p + 2048, enc(acc1[0], tag), enc(acc1[1], tag));
            st2(p + 3072, enc(acc1[2], tag), enc(acc1[3], tag));
        }
    }
    bar_arrive(BAR_A, 288);
}

}

namespace c6 {

constexpr int CS = 6;
constexpr int NCL = 16;
constexpr int NCTA = NCL * CS;
constexpr int NTHREADS = 416;
constexpr int NST = 11;

constexpr int SM_P = NST * STAGE_BYTES;
constexpr int SM_XS = SM_P;
constexpr int SM_YS = SM_P + 8256;
constexpr int SM_OS = SM_P;
constexpr int SM_QS = SM_P + 22528;
constexpr int SM_HS = SM_QS + 2304;
constexpr int SM_RED = SM_HS + 5248;
constexpr int SM_MX = SM_RED + 2048;
constexpr int SM_LS = SM_MX + 256;
constexpr int SM_F = SM_LS + 256;
constexpr int SM_G = SM_F + 32;
constexpr int SM_ST = SM_G + 16;
constexpr int SM_OR = SM_ST + 384;
constexpr int SM_XR = SM_OR + 6144;
constexpr int SM_BAR = SM_XR + 6144;
constexpr int SM_FLAG = SM_BAR + (2 * NST + 5) * 8;
constexpr int SM_TOTAL = SM_FLAG + 8;
constexpr int SM_ALLOC = SM_TOTAL + 1024;
constexpr int HS_STRIDE = 1312;
constexpr int OS_STRIDE = 1568;
constexpr int BAR_Y = BAR_X;
constexpr int BAR_HELP = BAR_ML;

#define CAP6 5
#define LEAD6 3
#define OG_GAP 100
#define OG6_DELAY 300
#define PT6 660
constexpr uint32_t P_B = PT6 * 192;
#define PACE_L PT6
constexpr uint32_t P_L = PACE_L * 192;
constexpr uint32_t P_52 = (uint32_t)((long long)P_B * (316 - 6 * LEAD6) / (6 * (52 - LEAD6)));
constexpr uint32_t P_54 = (uint32_t)((long long)P_B * (316 - 6 * LEAD6) / (6 * (54 - LEAD6)));
#define OFF6 400

constexpr int G_EPOCH = 0;
constexpr int G_Q = G_EPOCH + 128 * 4;
constexpr int G_H = G_Q + 2 * 4 * 4096;
constexpr int G_O = G_H + 2 * 4 * 4096;
constexpr int G_TOTAL = G_O + 4 * 4096;
__device__ __align__(1024) unsigned int g_scratch[G_TOTAL];

#define KTW(w, i)
#define KTA(i)

__device__ __forceinline__ void load_b(uint2 (&b)[4], uint32_t b_addr, bool bvalid) {
#pragma unroll
    for (int ks = 0; ks < 4; ks++) b[ks] = bvalid ? lds64(b_addr + ks * 32) : make_uint2(0u, 0u);
}
__device__ __forceinline__ void st_async2(uint32_t addr, float a, float b, uint32_t bar) {
    asm volatile("st.async.weak.shared::cluster.mbarrier::complete_tx::bytes.v2.f32 [%0], {%1, %2}, [%3];"
                 ::"r"(addr), "f"(a), "f"(b), "r"(bar) : "memory");
}
__device__ __forceinline__ void st_async4(uint32_t addr, float a, float b, float c, float d, uint32_t bar) {
    asm volatile("st.async.weak.shared::cluster.mbarrier::complete_tx::bytes.v4.f32 [%0], {%1, %2, %3, %4}, [%5];"
                 ::"r"(addr), "f"(a), "f"(b), "f"(c), "f"(d), "r"(bar) : "memory");
}
__device__ __forceinline__ uint32_t mapa(uint32_t addr, uint32_t rank) {
    uint32_t r;
    asm volatile("mapa.shared::cluster.u32 %0, %1, %2;" : "=r"(r) : "r"(addr), "r"(rank));
    return r;
}

__global__ void __launch_bounds__(NTHREADS, 1)
fused_kernel(const __nv_bfloat16* __restrict__ wq, const __nv_bfloat16* __restrict__ x, unsigned int* __restrict__ scr,
             __nv_bfloat16* __restrict__ out, const __nv_bfloat16* __restrict__ gate_w, const __nv_bfloat16* __restrict__ b1,
             const __grid_constant__ TMaps maps, const __nv_bfloat16* __restrict__ b2) {
    extern __shared__ unsigned char smem_raw[];
    const uint32_t sbase = (smem_u32(smem_raw) + 1023u) & ~1023u;
    unsigned char* sptr = smem_raw + (sbase - smem_u32(smem_raw));
    volatile uint32_t* flag = reinterpret_cast<volatile uint32_t*>(sptr + SM_FLAG);

    const int c = blockIdx.x;
    const int tid = threadIdx.x;
    const int warp = tid >> 5;
    const int lane = tid & 31;
    const int cl = c / CS, r = c - cl * CS;
    const int u0 = 8 * cl + (r < 2 ? 2 * r : r + 2);
    const int v0 = 7 * cl + 2 * (r - 2);
    const int nblk = 22 - ((0x0021100 >> (4 * r)) & 3);
    const int n2 = r < 4 ? 5 : 4;
    const int w2_0 = min(5 * r, 24), wo_0 = 5 * r + (r == 5);
    const uint32_t bar_full = sbase + SM_BAR;
    const uint32_t bar_empty = sbase + SM_BAR + NST * 8;
    const uint32_t bar_st = sbase + SM_BAR + 2 * NST * 8;
    const uint32_t bar_or = bar_st + 8;
    const uint32_t bar_xr = bar_st + 24;

    KTW(0, 0);
    if (warp == 8) {
        uint32_t t0 = 0;
        if (lane == 0) {
#pragma unroll
            for (int j = 0; j < LEAD6; j++) mbar_init(bar_full + j * 8, 1);
            asm volatile("fence.mbarrier_init.release.cluster;" ::: "memory");
            asm volatile("fence.proxy.async.shared::cta;" ::: "memory");
#pragma unroll
            for (int j = 0; j < LEAD6; j++) {
                mbar_expect_tx(bar_full + j * 8, STAGE_BYTES);
                tma_3d(sbase + j * STAGE_BYTES, &maps.wq3, 0, (u0 & 1) * 512 + j * 128, u0 >> 1, bar_full + j * 8);
            }
            t0 = gtime32() + OFF6 + (r * NCL + cl) * PT6 / 128;
#pragma unroll
            for (int i = LEAD6; i < NST; i++) mbar_init(bar_full + i * 8, 1);
#pragma unroll
            for (int i = 0; i < NST; i++) mbar_init(bar_empty + i * 8, 8);
#pragma unroll
            for (int i = 0; i < 5; i++) {
                mbar_init(bar_st + i * 8, 1);
                mbar_expect_tx(bar_st + i * 8, i == 0 ? 384 : 3072);
            }
            *flag = 0u;
            asm volatile("fence.mbarrier_init.release.cluster;" ::: "memory");
            asm volatile("fence.proxy.async.shared::cta;" ::: "memory");
            prefetch_tmap(&maps.w1n);
            prefetch_tmap(&maps.k);
            prefetch_tmap(&maps.v);
            prefetch_tmap(&maps.w2n);
            prefetch_tmap(&maps.won);
        }
        __syncwarp();
        asm volatile("barrier.cluster.arrive.relaxed.aligned;" ::: "memory");
        bar_arrive(BAR_INIT, NTHREADS);
        if (lane == 0) {
            const int kv_row0 = cl * SK + r * 64;
            uint32_t fb = bar_full + LEAD6 * 8, eph = 1u;
            uint32_t lb = bar_full + (LEAD6 + NST - CAP6) % NST * 8, lph = 1u;
            uint32_t due = t0 << 8;
#pragma unroll 1
            for (int phase = 0; phase < 7; phase++) {
                const CUtensorMap* map;
                int row, drow = 128, blk, n;
                uint32_t per = (r == 2 || r == 3) ? P_54 : P_52;
                if (phase == 0) {
                    map = &maps.wq3; row = (u0 & 1) * 512 + LEAD6 * 128; blk = u0 >> 1; n = 4 - LEAD6;
                } else if (phase < 3) {
                    const int unit = r < 2 ? u0 + 1 : v0 + phase - 1;
                    map = r < 2 ? &maps.wq3 : &maps.w1n; row = (unit & 1) * 512; blk = unit >> 1;
                    n = (phase == 2 && (r < 2 || r == 5)) ? 0 : 4;
                } else if (phase < 5) {
                    map = phase == 3 ? &maps.k : &maps.v; row = kv_row0; drow = 384; blk = 0; n = nblk;
                } else {
                    map = phase == 5 ? &maps.w2n : &maps.won; row = (phase == 5 ? w2_0 : wo_0) * 128; blk = cl;
                    n = phase == 5 ? n2 : 10 - n2; per = P_L;
                }
#pragma unroll 1
                for (int j = 0; j < n; j++) {
                    const uint32_t dst = sbase + (fb - bar_full) * (STAGE_BYTES / 8);
                    mbar_wait(lb, lph, flag);
                    mbar_wait(fb + NST * 8, eph, flag);
                    mbar_expect_tx(fb, STAGE_BYTES);
                    for (int it = 0; it < 100000 && (int)((gtime32() << 8) - due) < 0; it++) {}
                    tma_3d(dst, map, 0, row, blk, fb);
                    row += drow;
                    if (j == 20 && r == 5) row -= 7 * 64;
                    due += per;
                    fb += 8;
                    if (fb == bar_empty) { fb = bar_full; eph ^= 1u; }
                    lb += 8;
                    if (lb == bar_empty) { lb = bar_full; lph ^= 1u; }
                }
            }
            KTW(8, 13);
        }
        return;
    }
    asm volatile("barrier.cluster.arrive.relaxed.aligned;" ::: "memory");

    const int g = lane >> 2;
    const int t = lane & 3;
    const int mt = warp & 3;
    const int kh2 = warp >> 2;
    const uint32_t epoch = ld1(scr + G_EPOCH + c * 4) + 1u;
    asm volatile("prefetch.global.L2 [%0];" ::"l"(wq + (size_t)((u0 & 1) * 512 + (tid < 256 ? tid : tid - 32)) * 4096 + (u0 >> 1) * 64));
    const uint32_t tag = 1u + epoch % 3u;

    if (warp >= 9) {
        const int hb = warp - 9;
        const bool fin = r < 4 && hb < 2;
        const int col = cl * 64 + r * 16 + hb * 8 + (lane & 7);
        float b2v = 0.f;
        {
            uint4 xv[4], gw[4];
#pragma unroll
            for (int i = 0; i < 4; i++) xv[i] = __ldg(reinterpret_cast<const uint4*>(x) + hb * 128 + i * 32 + lane);
#pragma unroll
            for (int i = 0; i < 4; i++) gw[i] = __ldg(reinterpret_cast<const uint4*>(gate_w) + i * 32 + lane);
            if (fin) b2v = __bfloat162float(b2[col]);
            bar_sync(BAR_INIT, NTHREADS);
            float s0 = 0.f, s1 = 0.f, zs = 0.f;
#pragma unroll
            for (int i = 0; i < 4; i++) {
                const uint32_t xa[4] = {xv[i].x, xv[i].y, xv[i].z, xv[i].w};
                const uint32_t wa[4] = {gw[i].x, gw[i].y, gw[i].z, gw[i].w};
#pragma unroll
                for (int e = 0; e < 4; e++) {
                    s0 += bf_lo(xa[e]);
                    s1 += bf_hi(xa[e]);
                    zs += bf16r(bf_lo(xa[e]) * bf_lo(wa[e]));
                    zs += bf16r(bf_hi(xa[e]) * bf_hi(wa[e]));
                }
            }
            float s = s0 + s1;
#pragma unroll
            for (int o = 16; o > 0; o >>= 1) {
                s += __shfl_xor_sync(0xffffffffu, s, o);
                zs += __shfl_xor_sync(0xffffffffu, zs, o);
            }
            if (r >= 2) {
                const float mean = s * (1.0f / 1024.0f);
                float q0 = 0.f, q1 = 0.f;
#pragma unroll
                for (int i = 0; i < 4; i++) {
                    const uint32_t xa[4] = {xv[i].x, xv[i].y, xv[i].z, xv[i].w};
#pragma unroll
                    for (int e = 0; e < 4; e++) {
                        const float d0 = bf_lo(xa[e]) - mean, d1 = bf_hi(xa[e]) - mean;
                        q0 = fmaf(d0, d0, q0);
                        q1 = fmaf(d1, d1, q1);
                    }
                }
                float q = q0 + q1;
#pragma unroll
                for (int o = 16; o > 0; o >>= 1) q += __shfl_xor_sync(0xffffffffu, q, o);
                const float mb = bf16r(mean);
                const float vb = bf16r(q * (1.0f / 1024.0f));
                const float den = bf16r(sqrtf(bf16r(vb + 1e-5f)));
#pragma unroll
                for (int i = 0; i < 4; i++) {
                    const uint32_t xa[4] = {xv[i].x, xv[i].y, xv[i].z, xv[i].w};
                    uint32_t ya[4];
#pragma unroll
                    for (int e = 0; e < 4; e++) ya[e] = pack_bf16(bf16r(bf_lo(xa[e]) - mb) / den, bf16r(bf_hi(xa[e]) - mb) / den);
                    *reinterpret_cast<uint4*>(sptr + SM_YS + hb * XS_STRIDE + (i * 32 + lane) * 16) = make_uint4(ya[0], ya[1], ya[2], ya[3]);
                }
                bar_arrive(BAR_Y, 384);
            }
            zs = bf16r(zs);
            if (lane == 0) reinterpret_cast<float*>(sptr + SM_G)[hb] = bf16r(1.0f / (1.0f + __expf(-zs)));
        }
        const int sl = r + 6 * (hb - 2);
        const bool red_o = hb >= 2 && sl < 8;
        unsigned int* const o_dst = scr + G_O + cl * 1024 + g * 128 + sl * 16 + t * 4;
        bar_sync(BAR_HELP, 160);
        if (red_o) st4(o_dst, 0u, 0u, 0u, 0u);
        if (hb == 3) {
            mbar_wait_cluster(bar_st, flag);
            float4 d = make_float4(-INFINITY, 0.f, -INFINITY, 0.f);
            if (g < CS) d = *reinterpret_cast<const float4*>(sptr + SM_ST + lane * 16);
            float M0 = d.x, M1 = d.z;
#pragma unroll
            for (int o = 4; o < 32; o <<= 1) {
                M0 = fmaxf(M0, __shfl_xor_sync(0xffffffffu, M0, o));
                M1 = fmaxf(M1, __shfl_xor_sync(0xffffffffu, M1, o));
            }
            const float w0 = exp2f((d.x - M0) * 1.4426950408889634f), w1 = exp2f((d.z - M1) * 1.4426950408889634f);
            float L0 = w0 * d.y, L1 = w1 * d.w;
#pragma unroll
            for (int o = 4; o < 32; o <<= 1) {
                L0 += __shfl_xor_sync(0xffffffffu, L0, o);
                L1 += __shfl_xor_sync(0xffffffffu, L1, o);
            }
            if (g == r) *reinterpret_cast<float2*>(sptr + SM_F + t * 8) = make_float2(w0 / L0, w1 / L1);
            bar_arrive(BAR_F, 288);
        }
        {
            const unsigned int* p = scr + G_H + hb * 4096 + w2_0 * 128 + lane * 4;
            const uint32_t* pb = reinterpret_cast<const uint32_t*>(b1 + w2_0 * 128 + g * 16 + 2 * t);
#pragma unroll 1
            for (int i = 0; i < n2; i++) {
                const uint32_t ba = __ldg(pb + i * 64), bb = __ldg(pb + i * 64 + 4);
                uint4 d0, d1;
                for (uint32_t it = 0; it < POLL_LIMIT; it++) {
                    d0 = ld4(p + i * 128);
                    d1 = ld4(p + i * 128 + 4 * 4096);
                    if (warp_ok(bad4(d0, tag) | bad4(d1, tag))) break;
                    __nanosleep(200);
                }
                const float sv[4] = {dec(d0.x) + dec(d1.x), dec(d0.z) + dec(d1.z), dec(d0.y) + dec(d1.y), dec(d0.w) + dec(d1.w)};
                const float bv[4] = {bf_lo(ba), bf_hi(ba), bf_lo(bb), bf_hi(bb)};
                float h[4];
#pragma unroll
                for (int e = 0; e < 4; e++) {
                    const float v = bf16r(bf16r(sv[e]) + bv[e]);
                    const float inner = 0.7978845608028654f * (v + 0.044715f * v * v * v);
                    h[e] = 0.5f * v * (1.0f + tanhf(inner));
                }
                sts64(sbase + SM_HS + hb * HS_STRIDE + i * 256 + lane * 8, pack_bf16(h[0], h[1]), pack_bf16(h[2], h[3]));
            }
            KTW(9, 7);
            bar_arrive(BAR_HS, 384);
        }
        const float gate = reinterpret_cast<const float*>(sptr + SM_G)[lane >> 3];
        bar_sync(BAR_O, 384);
        if (red_o) {
            const float4* po = reinterpret_cast<const float4*>(sptr + SM_OR + (hb - 2) * 3072) + lane;
            mbar_wait_cluster(bar_or + (hb - 2) * 8, flag);
            float4 v[CS];
#pragma unroll
            for (int s = 0; s < CS; s++) v[s] = po[s * 32];
            const float o0 = ((v[0].x + v[1].x) + (v[2].x + v[3].x)) + (v[4].x + v[5].x);
            const float o1 = ((v[0].y + v[1].y) + (v[2].y + v[3].y)) + (v[4].y + v[5].y);
            const float o2 = ((v[0].z + v[1].z) + (v[2].z + v[3].z)) + (v[4].z + v[5].z);
            const float o3 = ((v[0].w + v[1].w) + (v[2].w + v[3].w)) + (v[4].w + v[5].w);
            st4(o_dst, __float_as_uint(bf16r(o0)) | tag, __float_as_uint(bf16r(o1)) | tag, __float_as_uint(bf16r(o2)) | tag,
                __float_as_uint(bf16r(o3)) | tag);
            KTW(11, 28);
        }
        __nanosleep(OG6_DELAY);
        {
            const unsigned int* po = scr + G_O + hb * 4096 + wo_0 * 128 + lane * 4;
            uint4 d[6];
            uint32_t pend = r < 4 ? 0x1fu : 0x3fu;
            for (uint32_t it = 0; it < POLL_LIMIT; it++) {
#pragma unroll
                for (int s = 0; s < 6; s++)
                    if (pend & (1u << s)) d[s] = ld4(po + s * 128);
#pragma unroll
                for (int s = 0; s < 6; s++) {
                    if ((pend & (1u << s)) && warp_ok(bad4(d[s], tag))) {
                        pend &= ~(1u << s);
                        sts64(sbase + SM_OS + hb * OS_STRIDE + s * 256 + lane * 8, __byte_perm(d[s].x, d[s].z, 0x7632),
                              __byte_perm(d[s].y, d[s].w, 0x7632));
                    }
                }
                if (pend == 0u) {
                    break;
                }
                __nanosleep(OG_GAP);
            }
            KTA(15);
            bar_arrive(BAR_OS, 384);
        }
        if (fin) {
            const float gm = bf16r(1.0f - gate);
            float term[2];
#pragma unroll
            for (int br = 0; br < 2; br++) {
                const float* xr = reinterpret_cast<const float*>(sptr + SM_XR) + br * 768 + hb * 32 + (lane & 7) * 4 + (lane >> 3);
                mbar_wait_cluster(bar_xr + br * 8, flag);
                KTW(9, 10 + br);
                float v[12];
#pragma unroll
                for (int s = 0; s < 12; s++) v[s] = xr[s * 64];
#pragma unroll
                for (int s = 0; s < 6; s++) v[s] += v[s + 6];
                const float sum = bf16r(((v[0] + v[1]) + (v[2] + v[3])) + (v[4] + v[5]));
                term[br] = br == 0 ? bf16r(gm * bf16r(sum + b2v)) : bf16r(gate * sum);
            }
            out[(lane >> 3) * D_MODEL + col] = __float2bfloat16_rn(term[1] + term[0]);
        }
        KTW(9, 12);
        return;
    }

    {
        const uint4 x0 = __ldg(reinterpret_cast<const uint4*>(x) + tid);
        const uint4 x1 = __ldg(reinterpret_cast<const uint4*>(x) + 256 + tid);
        if (t < 2 && (kh2 == 0 || r < 2)) {
            unsigned int* const q_dst = scr + G_Q + (((u0 + kh2) & 1) * 4 + 2 * t) * 4096 + (u0 >> 1) * 64 + mt * 16 + 2 * g;
            st2(q_dst, 0u, 0u);
            st2(q_dst + 4096, 0u, 0u);
        }
        *reinterpret_cast<uint4*>(sptr + SM_XS + (tid >> 7) * XS_STRIDE + (tid & 127) * 16) = x0;
        *reinterpret_cast<uint4*>(sptr + SM_XS + (2 + (tid >> 7)) * XS_STRIDE + (tid & 127) * 16) = x1;
    }
    bar_sync(BAR_INIT, NTHREADS);

    int stage = 0;
    uint32_t ph = 0;
    const uint32_t l8 = lane & 7;
    const uint32_t rowT = (l8 + 8 * (lane >> 4)) * 128;
    const uint32_t offT = rowT + ((((uint32_t)(2 * mt + ((lane >> 3) & 1))) ^ l8) << 4);
    const uint32_t aoff = sbase + kh2 * 8192 + offT;
    const bool bvalid = g < 4;

#pragma unroll 1
    for (int ui = 0; ui < ((r >= 2 && r <= 4) ? 3 : 2); ui++) {
        const bool isq = ui == 0 || r < 2;
        const int unit = isq ? u0 + ui : v0 + ui - 1;
        float4* const red = reinterpret_cast<float4*>(sptr + SM_RED) + (ui & 1) * 64 + mt * 16 + (g * 2 + (t & 1));
        unsigned int* const dst = scr + (isq ? G_Q : G_H) + ((unit & 1) * 4 + 2 * t) * 4096 + (unit >> 1) * 64 + mt * 16 + 2 * g;
        float acc0[4] = {0.f, 0.f, 0.f, 0.f}, acc1[4] = {0.f, 0.f, 0.f, 0.f};
        const uint32_t baddr = sbase + (isq ? SM_XS : SM_YS) + (g & 3) * XS_STRIDE + ((unit & 1) * 512 + kh2 * 64 + 2 * t) * 2;
        if (ui == 1 && r >= 2) bar_sync(BAR_Y, 384);
#pragma unroll 1
        for (int j = 0; j < 4; j++) {
            mbar_wait(bar_full + stage * 8, ph, flag);
            gemv_tile4(acc0, acc1, aoff + stage * STAGE_BYTES, baddr + j * 256, bvalid);
            __syncwarp();
            if (lane == 0) mbar_arrive_cnt(bar_empty + stage * 8, 1);
            if (++stage == NST) { stage = 0; ph ^= 1u; }
        }
        if (kh2 == 1 && t < 2) *red = make_float4(acc0[0] + acc1[0], acc0[1] + acc1[1], acc0[2] + acc1[2], acc0[3] + acc1[3]);
        bar_sync(BAR_PAIR + mt, 64);
        if (kh2 == 0 && t < 2) {
            const float4 o = *red;
            st2(dst, enc(acc0[0] + acc1[0] + o.x, tag), enc(acc0[2] + acc1[2] + o.z, tag));
            st2(dst + 4096, enc(acc0[1] + acc1[1] + o.y, tag), enc(acc0[3] + acc1[3] + o.w, tag));
        }
    }
    KTW(0, 1);
    mbar_wait(bar_full + stage * 8, ph, flag);
    uint32_t qf[8][2];
    {
        const unsigned int* p = scr + G_Q + cl * 1024 + tid * 4;
        uint4 d0, d1;
        for (uint32_t it = 0; it < POLL_LIMIT; it++) {
            d0 = ld4(p);
            d1 = ld4(p + 4 * 4096);
            if (warp_ok(bad4(d0, tag) | bad4(d1, tag))) break;
            __nanosleep(200);
        }
        sts64(sbase + SM_QS + warp * FR_STRIDE + lane * 8,
              pack_bf16(dec(d0.x) + dec(d1.x), dec(d0.z) + dec(d1.z)), pack_bf16(dec(d0.y) + dec(d1.y), dec(d0.w) + dec(d1.w)));
        bar_sync(BAR_CONS, 256);
#pragma unroll
        for (int ks = 0; ks < 8; ks++) {
            const uint2 v = lds64(sbase + SM_QS + g * FR_STRIDE + (ks * 4 + t) * 8);
            qf[ks][0] = v.x;
            qf[ks][1] = v.y;
        }
    }
    KTW(0, 2);
    {
        float sc[11][4];
        const bool full = nblk - kh2 >= 21;
        {
            int st = stage + kh2;
            uint32_t php = ph;
            if (st >= NST) { st -= NST; php ^= 1u; }
            const uint32_t krow = mt * 16 + l8 + 8 * ((lane >> 3) & 1);
            const uint32_t khi = lane >> 4;
#pragma unroll
            for (int i = 0; i < 11; i++) {
                if (i < 10 || full) {
                    mbar_wait(bar_full + st * 8, php, flag);
                    const uint32_t base = sbase + st * STAGE_BYTES + krow * 128;
                    float c0[4] = {0.f, 0.f, 0.f, 0.f}, c1[4] = {0.f, 0.f, 0.f, 0.f};
                    uint32_t a[8][4];
#pragma unroll
                    for (int ks = 0; ks < 8; ks++)
                        ldsm_x4(a[ks], base + (ks >> 2) * 8192 + (((uint32_t)((ks & 3) * 2) + khi) ^ l8) * 16);
#pragma unroll
                    for (int ks = 0; ks < 8; ks++) {
                        if (ks & 1) mma16816(c1, a[ks], qf[ks][0], qf[ks][1]);
                        else mma16816(c0, a[ks], qf[ks][0], qf[ks][1]);
                    }
                    __syncwarp();
                    if (lane == 0) mbar_arrive_cnt(bar_empty + st * 8, 2);
#pragma unroll
                    for (int e = 0; e < 4; e++) sc[i][e] = bf16r(bf16r(c0[e] + c1[e]) * 0.08838834764831845f);
                    st += 2;
                    if (st >= NST) { st -= NST; php ^= 1u; }
                } else {
#pragma unroll
                    for (int e = 0; e < 4; e++) sc[i][e] = sc[0][e];
                }
            }
            stage += nblk - NST;
            ph ^= 1u;
            if (stage >= NST) { stage -= NST; ph ^= 1u; }
        }
        KTW(0, 3);
        float m0 = sc[0][0], m1 = sc[0][1];
#pragma unroll
        for (int i = 0; i < 11; i++) {
            m0 = fmaxf(m0, fmaxf(sc[i][0], sc[i][2]));
            m1 = fmaxf(m1, fmaxf(sc[i][1], sc[i][3]));
        }
#pragma unroll
        for (int o = 4; o < 32; o <<= 1) {
            m0 = fmaxf(m0, __shfl_xor_sync(0xffffffffu, m0, o));
            m1 = fmaxf(m1, __shfl_xor_sync(0xffffffffu, m1, o));
        }
        float2* mx = reinterpret_cast<float2*>(sptr + SM_MX);
        if (g == 0) mx[warp * 4 + t] = make_float2(m0, m1);
        bar_sync(BAR_CONS, 256);
#pragma unroll
        for (int w = 0; w < 8; w++) {
            const float2 v = mx[w * 4 + t];
            m0 = fmaxf(m0, v.x);
            m1 = fmaxf(m1, v.y);
        }
        float l0 = 0.f, l1 = 0.f;
#pragma unroll
        for (int i = 0; i < 11; i++) {
            if (i < 10 || full) {
                const float e0 = exp2f((sc[i][0] - m0) * 1.4426950408889634f);
                const float e1 = exp2f((sc[i][1] - m1) * 1.4426950408889634f);
                const float e2 = exp2f((sc[i][2] - m0) * 1.4426950408889634f);
                const float e3 = exp2f((sc[i][3] - m1) * 1.4426950408889634f);
                l0 += e0 + e2;
                l1 += e1 + e3;
                const uint32_t key = (2 * i + kh2) * 64 + mt * 16 + g;
                sts32(sbase + SM_P + key * 16 + t * 4, pack_bf16(e0, e1));
                sts32(sbase + SM_P + (key + 8) * 16 + t * 4, pack_bf16(e2, e3));
            }
        }
#pragma unroll
        for (int o = 4; o < 32; o <<= 1) {
            l0 += __shfl_xor_sync(0xffffffffu, l0, o);
            l1 += __shfl_xor_sync(0xffffffffu, l1, o);
        }
        float2* ls = reinterpret_cast<float2*>(sptr + SM_LS);
        if (g == 0) ls[warp * 4 + t] = make_float2(l0, l1);
        bar_sync(BAR_CONS, 256);
        asm volatile("barrier.cluster.wait.acquire.aligned;" ::: "memory");
        if (warp == 0) {
            l0 = 0.f;
            l1 = 0.f;
#pragma unroll
            for (int w = 0; w < 8; w++) {
                const float2 v = ls[w * 4 + t];
                l0 += v.x;
                l1 += v.y;
            }
            if (g < CS) st_async4(mapa(sbase + SM_ST + r * 64 + t * 16, g), m0, l0, m1, l1, mapa(bar_st, g));
            bar_arrive(BAR_HELP, 160);
        }
    }
    {
        float acc0[4] = {0.f, 0.f, 0.f, 0.f}, acc1[4] = {0.f, 0.f, 0.f, 0.f};
        const uint32_t paddr = sbase + SM_P + lane * 16;
        const uint32_t sel = warp >= CS ? 1u : 0u;
        const uint32_t ro = mapa(sbase + SM_OR + sel * 3072 + r * 512 + t * 128 + g * 8, warp - sel * CS);
        const uint32_t rb = mapa(bar_or + sel * 8, warp - sel * CS);
#pragma unroll 1
        for (int j = 0; j < nblk; j++) {
            uint32_t pb[2][4];
            ldsm_x4_t(pb[0], paddr + j * 1024);
            ldsm_x4_t(pb[1], paddr + j * 1024 + 512);
            mbar_wait(bar_full + stage * 8, ph, flag);
            const uint32_t base = aoff + stage * STAGE_BYTES;
            uint32_t a[4][4];
#pragma unroll
            for (int ks = 0; ks < 4; ks++) ldsm_x4_t(a[ks], base + ks * 2048);
            mma16816(acc0, a[0], pb[0][0], pb[0][1]);
            mma16816(acc1, a[1], pb[0][2], pb[0][3]);
            mma16816(acc0, a[2], pb[1][0], pb[1][1]);
            mma16816(acc1, a[3], pb[1][2], pb[1][3]);
            __syncwarp();
            if (lane == 0) mbar_arrive_cnt(bar_empty + stage * 8, 1);
            if (++stage == NST) { stage = 0; ph ^= 1u; }
            if (j == nblk - 2) {
                bar_sync(BAR_F, 288);
                bar_sync(BAR_HS, 384);
            }
        }
        const float2 f = *reinterpret_cast<const float2*>(sptr + SM_F + t * 8);
        st_async2(ro, (acc0[0] + acc1[0]) * f.x, (acc0[2] + acc1[2]) * f.x, rb);
        st_async2(ro + 64, (acc0[1] + acc1[1]) * f.y, (acc0[3] + acc1[3]) * f.y, rb);
        bar_arrive(BAR_O, 384);
    }
    KTW(0, 4);
    const uint32_t ra = mapa(sbase + SM_XR + (r * 2 + kh2) * 256 + g * 16 + (t & 1) * 8, mt);
    const uint32_t rb = mapa(bar_xr, mt);
    uint32_t baddr = sbase + SM_HS + (g & 3) * HS_STRIDE + t * 8 + kh2 * 128;
#pragma unroll 1
    for (int br = 0; br < 2; br++) {
        float acc[4][4];
#pragma unroll
        for (int m = 0; m < 4; m++) acc[m][0] = acc[m][1] = acc[m][2] = acc[m][3] = 0.f;
        const int n = br == 0 ? n2 : 10 - n2;
#pragma unroll 1
        for (int j = 0; j < n; j++) {
            uint2 b[4];
            load_b(b, baddr + j * 256, bvalid);
            mbar_wait(bar_full + stage * 8, ph, flag);
            uint32_t a[4][4];
#pragma unroll
            for (int ks = 0; ks < 4; ks++) ldsm_x4_t(a[ks], aoff + stage * STAGE_BYTES + ks * 2048);
#pragma unroll
            for (int ks = 0; ks < 4; ks++) mma16816(acc[ks], a[ks], b[ks].x, b[ks].y);
            if (++stage == NST) { stage = 0; ph ^= 1u; }
        }
        if (t < 2) {
            st_async2(ra + br * 3072, (acc[0][0] + acc[1][0]) + (acc[2][0] + acc[3][0]), (acc[0][1] + acc[1][1]) + (acc[2][1] + acc[3][1]), rb + br * 8);
            st_async2(ra + br * 3072 + 128, (acc[0][2] + acc[1][2]) + (acc[2][2] + acc[3][2]), (acc[0][3] + acc[1][3]) + (acc[2][3] + acc[3][3]), rb + br * 8);
        }
        if (br == 0) {
            KTW(0, 5);
            baddr = sbase + SM_OS + (g & 3) * OS_STRIDE + t * 8 + kh2 * 128;
            bar_sync(BAR_OS, 384);
        }
    }
    if (tid == 0) *reinterpret_cast<volatile unsigned int*>(scr + G_EPOCH + c * 4) = epoch;
}

}
typedef CUresult (*EncodeFn)(CUtensorMap*, CUtensorMapDataType, cuuint32_t, void*, const cuuint64_t*, const cuuint64_t*,
                             const cuuint32_t*, const cuuint32_t*, CUtensorMapInterleave, CUtensorMapSwizzle,
                             CUtensorMapL2promotion, CUtensorMapFloatOOBfill);

void make_2d(EncodeFn enc_fn, CUtensorMap* tm, void* base, uint64_t cols, uint64_t rows, uint32_t box_rows) {
    cuuint64_t gd[2] = {cols, rows};
    cuuint64_t gs[1] = {cols * 2};
    cuuint32_t bd[2] = {64, box_rows};
    cuuint32_t es[2] = {1, 1};
    enc_fn(tm, CU_TENSOR_MAP_DATA_TYPE_BFLOAT16, 2, base, gd, gs, bd, es, CU_TENSOR_MAP_INTERLEAVE_NONE,
           CU_TENSOR_MAP_SWIZZLE_128B, CU_TENSOR_MAP_L2_PROMOTION_L2_128B, CU_TENSOR_MAP_FLOAT_OOB_FILL_NONE);
}
void make_3d(EncodeFn enc_fn, CUtensorMap* tm, void* base, uint64_t cols, uint64_t rows, uint32_t box_rows, uint32_t box_blocks) {
    cuuint64_t gd[3] = {64, rows, cols / 64};
    cuuint64_t gs[2] = {cols * 2, 128};
    cuuint32_t bd[3] = {64, box_rows, box_blocks};
    cuuint32_t es[3] = {1, 1, 1};
    enc_fn(tm, CU_TENSOR_MAP_DATA_TYPE_BFLOAT16, 3, base, gd, gs, bd, es, CU_TENSOR_MAP_INTERLEAVE_NONE,
           CU_TENSOR_MAP_SWIZZLE_128B, CU_TENSOR_MAP_L2_PROMOTION_L2_128B, CU_TENSOR_MAP_FLOAT_OOB_FILL_NONE);
}

}

extern "C" void kernel_launch(void* const* d_in, const int* in_sizes, int n_in, void* d_out, int out_size) {
    (void)in_sizes; (void)n_in; (void)out_size;
    static TMaps maps;
    static void* cached[6] = {nullptr, nullptr, nullptr, nullptr, nullptr, nullptr};
    static EncodeFn enc_fn = nullptr;
    static void* scr = nullptr;
    static bool use_c6 = false;
    cudaLaunchConfig_t cfg = {};
    cudaLaunchAttribute at[1];
    cfg.gridDim = dim3(c6::NCTA);
    cfg.blockDim = dim3(c6::NTHREADS);
    cfg.dynamicSmemBytes = c6::SM_ALLOC;
    cfg.stream = cudaStreamPerThread;
    at[0].id = cudaLaunchAttributeClusterDimension;
    at[0].val.clusterDim.x = c6::CS;
    at[0].val.clusterDim.y = 1;
    at[0].val.clusterDim.z = 1;
    cfg.attrs = at;
    cfg.numAttrs = 1;
    if (!enc_fn) {
        void* fn = nullptr;
        cudaDriverEntryPointQueryResult qr;
        cudaGetDriverEntryPoint("cuTensorMapEncodeTiled", &fn, cudaEnableDefault, &qr);
        enc_fn = (EncodeFn)fn;
        cudaFuncSetAttribute(fb::fused_kernel, cudaFuncAttributeMaxDynamicSharedMemorySize, fb::SM_ALLOC);
        cudaFuncSetAttribute(c6::fused_kernel, cudaFuncAttributeMaxDynamicSharedMemorySize, c6::SM_ALLOC);
        int ncl = 0;
        if (cudaOccupancyMaxActiveClusters(&ncl, c6::fused_kernel, &cfg) != cudaSuccess) { ncl = 0; (void)cudaGetLastError(); }
        use_c6 = ncl >= c6::NCL;
        if (use_c6) cudaGetSymbolAddress(&scr, c6::g_scratch);
        else cudaGetSymbolAddress(&scr, fb::g_scratch);
    }
    void* cur[6] = {d_in[3], d_in[6], d_in[1], d_in[2], d_in[8], d_in[4]};
    bool same = true;
    for (int i = 0; i < 6; i++) same = same && (cur[i] == cached[i]);
    if (!same) {
        make_2d(enc_fn, &maps.wq, d_in[3], 4096, 1024, 128);
        make_2d(enc_fn, &maps.w1, d_in[6], F_DIM, 1024, 128);
        make_3d(enc_fn, &maps.k, d_in[1], 128, 16 * SK, 64, 2);
        make_3d(enc_fn, &maps.v, d_in[2], 128, 16 * SK, 64, 2);
        make_3d(enc_fn, &maps.w2, d_in[8], 1024, F_DIM, 16, 4);
        make_3d(enc_fn, &maps.wo, d_in[4], 1024, 4096, 16, 4);
        make_3d(enc_fn, &maps.w2n, d_in[8], 1024, F_DIM, 128, 1);
        make_3d(enc_fn, &maps.wq3, d_in[3], 4096, 1024, 128, 1);
        make_3d(enc_fn, &maps.won, d_in[4], 1024, 4096, 128, 1);
        make_3d(enc_fn, &maps.w1n, d_in[6], F_DIM, 1024, 128, 1);
        for (int i = 0; i < 6; i++) cached[i] = cur[i];
    }
    if (use_c6) {
        cudaLaunchKernelEx(&cfg, c6::fused_kernel, (const __nv_bfloat16*)d_in[3], (const __nv_bfloat16*)d_in[0],
                           (unsigned int*)scr, (__nv_bfloat16*)d_out, (const __nv_bfloat16*)d_in[10],
                           (const __nv_bfloat16*)d_in[7], maps, (const __nv_bfloat16*)d_in[9]);
    } else {
        fb::fused_kernel<<<fb::NCTA, fb::NTHREADS, fb::SM_ALLOC, cudaStreamPerThread>>>(
            (const __nv_bfloat16*)d_in[3], (const __nv_bfloat16*)d_in[0], (unsigned int*)scr, (__nv_bfloat16*)d_out,
            (const __nv_bfloat16*)d_in[10], (const __nv_bfloat16*)d_in[7], maps, (const __nv_bfloat16*)d_in[9]);
    }
}
```

```cpp
#include <cuda_runtime.h>
#include <cuda.h>
#include <cuda_bf16.h>
#include <stdint.h>

namespace {

constexpr int NSTAGE = 12;
constexpr int STAGE_BYTES = 16384;

constexpr int D_MODEL = 1024;
constexpr int F_DIM = 3584;
constexpr int SK = 8192;

constexpr int XS_STRIDE = 1032 * 2;
constexpr int FR_STRIDE = 288;

#define PACE_T 652
#define PACE_LEAD 2
#define PACE_OFF PACE_T
#define PW_J 6
#define PACE_CAP 4
#define FP_GAP 160
#define OG_DELAY 400

constexpr int BAR_INIT = 0;
constexpr int BAR_CONS = 1;
constexpr int BAR_PAIR = 2;
constexpr int BAR_X = 6;
constexpr int BAR_ML = 7;
constexpr int BAR_O = 8;
constexpr int BAR_OS = 9;
constexpr int BAR_W1 = 10;
constexpr int BAR_HS = 11;
constexpr int BAR_A = 12;
constexpr int BAR_B = 13;
constexpr int BAR_F = 14;

struct TMaps {
    CUtensorMap wq, w1, k, v, w2, wo, w2n, w1n, wq3, won;
};

__device__ __forceinline__ uint32_t smem_u32(const void* p) { return (uint32_t)__cvta_generic_to_shared(p); }
__device__ __forceinline__ uint32_t gtime32() { uint32_t t; asm volatile("mov.u32 %0, %globaltimer_lo;" : "=r"(t)); return t; }

__device__ __forceinline__ void mbar_init(uint32_t bar, uint32_t cnt) {
    asm volatile("mbarrier.init.shared::cta.b64 [%0], %1;" ::"r"(bar), "r"(cnt) : "memory");
}
__device__ __forceinline__ void mbar_expect_tx(uint32_t bar, uint32_t bytes) {
    asm volatile("mbarrier.arrive.expect_tx.shared::cta.b64 _, [%0], %1;" ::"r"(bar), "r"(bytes) : "memory");
}
__device__ __forceinline__ void mbar_arrive_cnt(uint32_t bar, uint32_t cnt) {
    asm volatile("mbarrier.arrive.shared::cta.b64 _, [%0], %1;" ::"r"(bar), "r"(cnt) : "memory");
}
__device__ __forceinline__ bool mbar_try(uint32_t bar, uint32_t parity) {
    uint32_t ok;
    asm volatile(
        "{\n.reg .pred p;\n"
        "mbarrier.try_wait.parity.shared::cta.b64 p, [%1], %2;\n"
        "selp.u32 %0, 1, 0, p;\n}\n"
        : "=r"(ok)
        : "r"(bar), "r"(parity)
        : "memory");
    return ok != 0;
}
__device__ __noinline__ void mbar_wait_slow(uint32_t bar, uint32_t parity, volatile uint32_t* flag) {
    long long t0 = clock64();
    for (uint32_t it = 0; it < 0x40000000u; it++) {
        if (mbar_try(bar, parity)) return;
        if ((it & 63u) == 63u) {
            if (*flag) return;
            if (clock64() - t0 > 2000000000LL) { *flag = 1u; return; }
        }
    }
}
__device__ __forceinline__ void mbar_wait(uint32_t bar, uint32_t parity, volatile uint32_t* flag) {
    if (mbar_try(bar, parity)) return;
    if (mbar_try(bar, parity)) return;
    mbar_wait_slow(bar, parity, flag);
}

__device__ __forceinline__ void mbar_wait_cluster(uint32_t bar, volatile uint32_t* flag) {
    const long long t0 = clock64();
    for (uint32_t it = 0; it < 0x40000000u; it++) {
        uint32_t ok;
        asm volatile(
            "{\n.reg .pred p;\n"
            "mbarrier.try_wait.parity.acquire.cluster.shared::cta.b64 p, [%1], 0;\n"
            "selp.u32 %0, 1, 0, p;\n}\n"
            : "=r"(ok)
            : "r"(bar)
            : "memory");
        if (ok) return;
        if ((it & 63u) == 63u && (*flag || clock64() - t0 > 4000000000LL)) return;
    }
}

__device__ __forceinline__ void tma_2d(uint32_t dst, const CUtensorMap* tm, int c0, int c1, uint32_t bar) {
    asm volatile(
        "cp.async.bulk.tensor.2d.shared::cluster.global.mbarrier::complete_tx::bytes.L2::cache_hint [%0], [%1, {%3, %4}], [%2], %5;"
        ::"r"(dst), "l"(tm), "r"(bar), "r"(c0), "r"(c1), "l"(0x12F0000000000000ull)
        : "memory");
}
__device__ __forceinline__ void tma_3d(uint32_t dst, const CUtensorMap* tm, int c0, int c1, int c2, uint32_t bar) {
    asm volatile(
        "cp.async.bulk.tensor.3d.shared::cluster.global.mbarrier::complete_tx::bytes.L2::cache_hint [%0], [%1, {%3, %4, %5}], [%2], %6;"
        ::"r"(dst), "l"(tm), "r"(bar), "r"(c0), "r"(c1), "r"(c2), "l"(0x12F0000000000000ull)
        : "memory");
}
__device__ __forceinline__ void bulk_load(uint32_t dst, const void* src, uint32_t bytes, uint32_t bar) {
    asm volatile("cp.async.bulk.shared::cluster.global.mbarrier::complete_tx::bytes [%0], [%1], %2, [%3];"
                 ::"r"(dst), "l"(src), "r"(bytes), "r"(bar)
                 : "memory");
}
__device__ __forceinline__ void prefetch_tmap(const CUtensorMap* tm) {
    asm volatile("prefetch.tensormap [%0];" ::"l"(tm) : "memory");
}
__device__ __forceinline__ void bar_sync(int id, int cnt) { asm volatile("bar.sync %0, %1;" ::"r"(id), "r"(cnt) : "memory"); }
__device__ __forceinline__ void bar_arrive(int id, int cnt) { asm volatile("bar.arrive %0, %1;" ::"r"(id), "r"(cnt) : "memory"); }

__device__ __forceinline__ void ldsm_x4(uint32_t (&r)[4], uint32_t addr) {
    asm volatile("ldmatrix.sync.aligned.m8n8.x4.shared.b16 {%0,%1,%2,%3}, [%4];"
                 : "=r"(r[0]), "=r"(r[1]), "=r"(r[2]), "=r"(r[3])
                 : "r"(addr)
                 : "memory");
}
__device__ __forceinline__ void ldsm_x4_t(uint32_t (&r)[4], uint32_t addr) {
    asm volatile("ldmatrix.sync.aligned.m8n8.x4.trans.shared.b16 {%0,%1,%2,%3}, [%4];"
                 : "=r"(r[0]), "=r"(r[1]), "=r"(r[2]), "=r"(r[3])
                 : "r"(addr)
                 : "memory");
}
__device__ __forceinline__ void mma16816(float (&c)[4], const uint32_t (&a)[4], uint32_t b0, uint32_t b1) {
    asm volatile(
        "mma.sync.aligned.m16n8k16.row.col.f32.bf16.bf16.f32 {%0,%1,%2,%3}, {%4,%5,%6,%7}, {%8,%9}, {%0,%1,%2,%3};"
        : "+f"(c[0]), "+f"(c[1]), "+f"(c[2]), "+f"(c[3])
        : "r"(a[0]), "r"(a[1]), "r"(a[2]), "r"(a[3]), "r"(b0), "r"(b1));
}
__device__ __forceinline__ uint32_t lds32(uint32_t addr) {
    uint32_t v;
    asm volatile("ld.shared.b32 %0, [%1];" : "=r"(v) : "r"(addr) : "memory");
    return v;
}
__device__ __forceinline__ uint2 lds64(uint32_t addr) {
    uint2 v;
    asm volatile("ld.shared.v2.b32 {%0, %1}, [%2];" : "=r"(v.x), "=r"(v.y) : "r"(addr) : "memory");
    return v;
}
__device__ __forceinline__ void sts32(uint32_t addr, uint32_t v) {
    asm volatile("st.shared.b32 [%0], %1;" ::"r"(addr), "r"(v) : "memory");
}
__device__ __forceinline__ void sts64(uint32_t addr, uint32_t a, uint32_t b) {
    asm volatile("st.shared.v2.b32 [%0], {%1, %2};" ::"r"(addr), "r"(a), "r"(b) : "memory");
}

__device__ __forceinline__ float bf16r(float x) { return __bfloat162float(__float2bfloat16_rn(x)); }
__device__ __forceinline__ uint32_t pack_bf16(float lo, float hi) {
    __nv_bfloat162 v = __floats2bfloat162_rn(lo, hi);
    return *reinterpret_cast<uint32_t*>(&v);
}
__device__ __forceinline__ float bf_lo(uint32_t u) { return __uint_as_float(u << 16); }
__device__ __forceinline__ float bf_hi(uint32_t u) { return __uint_as_float(u & 0xffff0000u); }

__device__ __forceinline__ uint32_t enc(float v, uint32_t tag) { return (__float_as_uint(v) & ~3u) | tag; }
__device__ __forceinline__ float dec(uint32_t u) { return __uint_as_float(u & ~3u); }
__device__ __forceinline__ void st2(unsigned int* p, uint32_t a, uint32_t b) {
    asm volatile("st.relaxed.gpu.global.v2.b32 [%0], {%1, %2};" ::"l"(p), "r"(a), "r"(b) : "memory");
}
__device__ __forceinline__ void st4(unsigned int* p, uint32_t a, uint32_t b, uint32_t c, uint32_t d) {
    asm volatile("st.relaxed.gpu.global.v4.b32 [%0], {%1, %2, %3, %4};" ::"l"(p), "r"(a), "r"(b), "r"(c), "r"(d) : "memory");
}
__device__ __forceinline__ uint32_t ld1(const unsigned int* p) {
    uint32_t v;
    asm volatile("ld.relaxed.gpu.global.b32 %0, [%1];" : "=r"(v) : "l"(p) : "memory");
    return v;
}
__device__ __forceinline__ uint2 ld2(const unsigned int* p) {
    uint2 v;
    asm volatile("ld.relaxed.gpu.global.v2.b32 {%0, %1}, [%2];" : "=r"(v.x), "=r"(v.y) : "l"(p) : "memory");
    return v;
}
__device__ __forceinline__ uint4 ld4(const unsigned int* p) {
    uint4 v;
    asm volatile("ld.relaxed.gpu.global.v4.b32 {%0, %1, %2, %3}, [%4];" : "=r"(v.x), "=r"(v.y), "=r"(v.z), "=r"(v.w) : "l"(p) : "memory");
    return v;
}
__device__ __forceinline__ uint32_t bad4(const uint4& v, uint32_t tag) { return (v.x ^ tag) | (v.y ^ tag) | (v.z ^ tag) | (v.w ^ tag); }
__device__ __forceinline__ bool warp_ok(uint32_t bad) { return __all_sync(0xffffffffu, (bad & 3u) == 0u); }
__device__ __forceinline__ void spin_cycles(int n) {
    const uint32_t t0 = (uint32_t)clock64();
    for (int it = 0; it < 1000 && (int)((uint32_t)clock64() - t0) < n; it++) {}
}
constexpr uint32_t POLL_LIMIT = 1u << 21;

__device__ __forceinline__ void gemv_tile4(float (&acc0)[4], float (&acc1)[4], uint32_t a_addr, uint32_t b_addr, bool bvalid) {
    uint32_t a[4][4];
    uint32_t b[4][2];
#pragma unroll
    for (int ks = 0; ks < 4; ks++) ldsm_x4_t(a[ks], a_addr + ks * 2048);
#pragma unroll
    for (int ks = 0; ks < 4; ks++) {
        b[ks][0] = bvalid ? lds32(b_addr + ks * 32) : 0u;
        b[ks][1] = bvalid ? lds32(b_addr + ks * 32 + 16) : 0u;
    }
#pragma unroll
    for (int ks = 0; ks < 4; ks++) {
        if (ks & 1) mma16816(acc1, a[ks], b[ks][0], b[ks][1]);
        else mma16816(acc0, a[ks], b[ks][0], b[ks][1]);
    }
}

template <int N>
__device__ __forceinline__ float final_sum(const unsigned int* buf, int lane, uint32_t tag, bool backoff) {
    const unsigned int* p = buf + (lane >> 3) * (N * 32) + (lane & 7) * 4;
    uint4 d[N];
    for (uint32_t it = 0; it < POLL_LIMIT; it++) {
        uint32_t bad = 0;
#pragma unroll
        for (int i = 0; i < N; i++) { d[i] = ld4(p + i * 32); bad |= bad4(d[i], tag); }
        if (warp_ok(bad)) break;
        if (backoff) __nanosleep(100);
    }
    float s0 = 0.f, s1 = 0.f, s2 = 0.f, s3 = 0.f;
#pragma unroll
    for (int i = 0; i < N; i++) { s0 += dec(d[i].x); s1 += dec(d[i].y); s2 += dec(d[i].z); s3 += dec(d[i].w); }
    const bool hi = lane & 16;
    float u0 = hi ? s0 : s2, u1 = hi ? s1 : s3;
    float k0 = hi ? s2 : s0, k1 = hi ? s3 : s1;
    k0 += __shfl_xor_sync(0xffffffffu, u0, 16);
    k1 += __shfl_xor_sync(0xffffffffu, u1, 16);
    const bool od = lane & 8;
    const float w = od ? k0 : k1;
    float r = od ? k1 : k0;
    r += __shfl_xor_sync(0xffffffffu, w, 8);
    return r;
}

namespace fb {

constexpr int NCTA = 128;
constexpr int NTHREADS = 416;

constexpr int SM_P = NSTAGE * STAGE_BYTES;
constexpr int SM_XS = SM_P;
constexpr int SM_YS = SM_P + 16384;
constexpr int SM_QS = SM_YS + 4160;
constexpr int SM_OS = SM_QS + 2304;
constexpr int SM_HS = SM_OS + 1152;
constexpr int SM_RED = SM_HS + 960;
constexpr int SM_MX = SM_RED + 2048;
constexpr int SM_LS = SM_MX + 256;
constexpr int SM_F = SM_LS + 256;
constexpr int SM_BAR = SM_F + 32;
constexpr int SM_FLAG = SM_BAR + 2 * NSTAGE * 8;
constexpr int SM_TOTAL = SM_FLAG + 8;
constexpr int SM_ALLOC = SM_TOTAL + 1024;

constexpr int YS_STRIDE = 520 * 2;
constexpr int HS_STRIDE = 240;

constexpr int G_EPOCH = 0;
constexpr int G_Q = G_EPOCH + NCTA * 4;
constexpr int G_H = G_Q + 2 * 4 * 4096;
constexpr int G_ML = G_H + 2 * F_DIM * 4;
constexpr int G_O = G_ML + NCTA * 16;
constexpr int G_A = G_O + NCTA * 1024;
constexpr int G_B = G_A + NCTA * 1024;
constexpr int G_TOTAL = G_B + NCTA * 1024;
__device__ __align__(1024) unsigned int g_scratch[G_TOTAL];

__global__ void __launch_bounds__(NTHREADS, 1)
fused_kernel(const __nv_bfloat16* __restrict__ wq, const __nv_bfloat16* __restrict__ x, unsigned int* __restrict__ scr,
             __nv_bfloat16* __restrict__ out, const __nv_bfloat16* __restrict__ gate_w, const __nv_bfloat16* __restrict__ b1,
             const __grid_constant__ TMaps maps, const __nv_bfloat16* __restrict__ b2) {
    extern __shared__ unsigned char smem_raw[];
    const uint32_t sbase = (smem_u32(smem_raw) + 1023u) & ~1023u;
    unsigned char* sptr = smem_raw + (sbase - smem_u32(smem_raw));
    volatile uint32_t* flag = reinterpret_cast<volatile uint32_t*>(sptr + SM_FLAG);

    const int c = blockIdx.x;
    const int tid = threadIdx.x;
    const int warp = tid >> 5;
    const int lane = tid & 31;
    const bool has_w1 = c < 112;
    const int kb = c >> 2, nb = c & 3;
    const uint32_t bar_full = sbase + SM_BAR;
    const uint32_t bar_empty = sbase + SM_BAR + NSTAGE * 8;

    if (warp == 8) {
        const int n_w1 = has_w1 ? 4 : 0;
        const int n_tiles = 44 + n_w1;
        const int kv_row0 = (c >> 3) * SK + (c & 7) * 1024;
        uint32_t due = 0;
        if (lane == 0) {
#pragma unroll
            for (int j = 0; j < PACE_LEAD; j++) mbar_init(bar_full + j * 8, 1);
            asm volatile("fence.mbarrier_init.release.cluster;" ::: "memory");
            asm volatile("fence.proxy.async.shared::cta;" ::: "memory");
#pragma unroll
            for (int j = 0; j < PACE_LEAD; j++) {
                mbar_expect_tx(bar_full + j * 8, STAGE_BYTES);
                tma_2d(sbase + j * STAGE_BYTES, &maps.wq, (c >> 1) * 64, (c & 1) * 512 + j * 128, bar_full + j * 8);
            }
            due = gtime32() + PACE_OFF + (c >> 1) * PACE_T / 64;
#pragma unroll
            for (int i = PACE_LEAD; i < NSTAGE; i++) mbar_init(bar_full + i * 8, 1);
#pragma unroll
            for (int i = 0; i < NSTAGE; i++) mbar_init(bar_empty + i * 8, 8);
            *flag = 0u;
            asm volatile("fence.mbarrier_init.release.cluster;" ::: "memory");
            asm volatile("fence.proxy.async.shared::cta;" ::: "memory");
            prefetch_tmap(&maps.w1);
            prefetch_tmap(&maps.k);
            prefetch_tmap(&maps.v);
            prefetch_tmap(&maps.w2);
            prefetch_tmap(&maps.wo);
        }
        __syncwarp();
        bar_arrive(BAR_INIT, NTHREADS);
        if (lane == 0) {
            int landed = 0;
            for (int i = PACE_LEAD; i < n_tiles; i++) {
                while (landed + PACE_CAP <= i) {
                    mbar_wait(bar_full + (landed % NSTAGE) * 8, (uint32_t)(landed / NSTAGE) & 1u, flag);
                    landed++;
                }
                const int stage = i % NSTAGE;
                if (i >= NSTAGE) mbar_wait(bar_empty + stage * 8, (uint32_t)(i / NSTAGE - 1) & 1u, flag);
                for (int it = 0; it < 100000 && (int)(gtime32() - due) < 0; it++) {}
                const uint32_t dst = sbase + stage * STAGE_BYTES;
                const uint32_t fb = bar_full + stage * 8;
                int j = i - 4;
                if (j < 0) {
                    mbar_expect_tx(fb, STAGE_BYTES);
                    tma_2d(dst, &maps.wq, (c >> 1) * 64, (c & 1) * 512 + i * 128, fb);
                    due += (j == -1 && !has_w1) ? PACE_T * 9 / 2 : PACE_T;
                } else if (j < n_w1) {
                    mbar_expect_tx(fb, STAGE_BYTES);
                    tma_2d(dst, &maps.w1, (c >> 1) * 64, (c & 1) * 512 + j * 128, fb);
                    due += PACE_T * 7 / 8;
                } else if (j < 32 + n_w1) {
                    j -= n_w1;
                    mbar_expect_tx(fb, STAGE_BYTES);
                    tma_3d(dst, j < 16 ? &maps.k : &maps.v, 0, kv_row0 + (j & 15) * 64, 0, fb);
                    due += PACE_T;
                } else {
                    j -= 32 + n_w1;
                    const CUtensorMap* tm = j < 4 ? &maps.w2 : &maps.wo;
                    const int row = j < 4 ? kb * 112 + j * 32 : kb * 128 + (j - 4) * 32;
                    mbar_expect_tx(fb, j != 3 ? STAGE_BYTES : STAGE_BYTES / 2);
                    tma_3d(dst, tm, 0, row, nb * 4, fb);
                    if (j != 3) tma_3d(dst + 8192, tm, 0, row + 16, nb * 4, fb);
                    due += j != 3 ? PACE_T : PACE_T / 2;
                }
            }
        }
        return;
    }

    const int g = lane >> 2;
    const int t = lane & 3;
    const int khalf = c & 1;
    const int pair = c >> 3;
    const int mt = warp & 3;
    const int kh2 = warp >> 2;
    const uint32_t epoch = ld1(scr + G_EPOCH + c * 4) + 1u;
    unsigned int* const q_dst = scr + G_Q + (khalf * 4 + 2 * t) * 4096 + (c >> 1) * 64 + mt * 16 + 2 * g;
    unsigned int* const h_dst = scr + G_H + (khalf * F_DIM + (c >> 1) * 64 + mt * 16 + g) * 4 + 2 * t;
    if (warp < 8) {
        asm volatile("prefetch.global.L2 [%0];" ::"l"(wq + (size_t)(khalf * 512 + tid) * 4096 + (c >> 1) * 64));
        const uint4 x0 = __ldg(reinterpret_cast<const uint4*>(x) + tid);
        const uint4 x1 = __ldg(reinterpret_cast<const uint4*>(x) + 256 + tid);
        if (warp < 4 && t < 2) {
            st2(q_dst, 0u, 0u);
            st2(q_dst + 4096, 0u, 0u);
            if (has_w1) {
                st2(h_dst, 0u, 0u);
                st2(h_dst + 32, 0u, 0u);
            }
        }
        *reinterpret_cast<uint4*>(sptr + SM_XS + (tid >> 7) * XS_STRIDE + (tid & 127) * 16) = x0;
        *reinterpret_cast<uint4*>(sptr + SM_XS + (2 + (tid >> 7)) * XS_STRIDE + (tid & 127) * 16) = x1;
    }
    const uint32_t tag = 1u + epoch % 3u;

    if (warp >= 9) {
        float gate = 0.f, b2v = 0.f;
        if (warp == 9) {
            uint4 gw[4];
#pragma unroll
            for (int i = 0; i < 4; i++) gw[i] = __ldg(reinterpret_cast<const uint4*>(gate_w) + i * 32 + lane);
            b2v = __bfloat162float(b2[c * 8 + (lane & 7)]);
            bar_sync(BAR_INIT, NTHREADS);
            float zz = 0.f;
#pragma unroll 1
            for (int b = 0; b < 4; b++) {
                float zs = 0.f;
#pragma unroll
                for (int i = 0; i < 4; i++) {
                    const uint4 xv = *reinterpret_cast<const uint4*>(sptr + SM_XS + b * XS_STRIDE + (i * 32 + lane) * 16);
                    const uint32_t xa[4] = {xv.x, xv.y, xv.z, xv.w};
                    const uint32_t wa[4] = {gw[i].x, gw[i].y, gw[i].z, gw[i].w};
#pragma unroll
                    for (int e = 0; e < 4; e++) {
                        zs += bf16r(bf_lo(xa[e]) * bf_lo(wa[e]));
                        zs += bf16r(bf_hi(xa[e]) * bf_hi(wa[e]));
                    }
                }
#pragma unroll
                for (int o = 16; o > 0; o >>= 1) zs += __shfl_xor_sync(0xffffffffu, zs, o);
                if ((lane >> 3) == b) zz = zs;
            }
            bar_arrive(BAR_X, 288);
            zz = bf16r(zz);
            gate = bf16r(1.0f / (1.0f + __expf(-zz)));
            if (lane == 0) *reinterpret_cast<volatile unsigned int*>(scr + G_EPOCH + c * 4) = epoch;
        } else if (warp == 11) {
            const bool has4 = lane < 16;
            float bias[4];
#pragma unroll
            for (int i = 0; i < 4; i++) bias[i] = (i < 3 || has4) ? __bfloat162float(b1[kb * 112 + i * 32 + lane]) : 0.f;
            bar_sync(BAR_INIT, NTHREADS);
            bar_sync(BAR_W1, 288);
            const unsigned int* p = scr + G_H + (kb * 112 + lane) * 4;
            uint4 d[4][2];
            for (uint32_t it = 0; it < POLL_LIMIT; it++) {
                __nanosleep(1000);
                uint32_t bad = 0;
#pragma unroll
                for (int i = 0; i < 4; i++) {
                    if (i < 3 || has4) {
                        d[i][0] = ld4(p + i * 128);
                        d[i][1] = ld4(p + i * 128 + F_DIM * 4);
                        bad |= bad4(d[i][0], tag) | bad4(d[i][1], tag);
                    }
                }
                if (warp_ok(bad)) break;
            }
#pragma unroll
            for (int i = 0; i < 4; i++) {
                if (i < 3 || has4) {
                    const int cl = i * 32 + lane;
                    const uint32_t u0[4] = {d[i][0].x, d[i][0].y, d[i][0].z, d[i][0].w};
                    const uint32_t u1[4] = {d[i][1].x, d[i][1].y, d[i][1].z, d[i][1].w};
#pragma unroll
                    for (int b = 0; b < 4; b++) {
                        float v = bf16r(dec(u0[b]) + dec(u1[b]));
                        v = bf16r(v + bias[i]);
                        const float inner = 0.7978845608028654f * (v + 0.044715f * v * v * v);
                        const float hv = 0.5f * v * (1.0f + tanhf(inner));
                        *reinterpret_cast<__nv_bfloat16*>(sptr + SM_HS + b * HS_STRIDE + cl * 2) = __float2bfloat16_rn(hv);
                    }
                }
            }
            bar_arrive(BAR_HS, 288);
        } else if (warp == 12) {
            bar_sync(BAR_INIT, NTHREADS);
            bar_sync(BAR_ML, 64);
            const unsigned int* p = scr + G_ML + pair * 128 + lane * 4;
            uint4 d;
            for (uint32_t it = 0; it < POLL_LIMIT; it++) {
                __nanosleep(1000);
                d = ld4(p);
                if (warp_ok(bad4(d, tag))) break;
            }
            const float m0 = dec(d.x), m1 = dec(d.z);
            float M0 = m0, M1 = m1;
#pragma unroll
            for (int o = 4; o < 32; o <<= 1) {
                M0 = fmaxf(M0, __shfl_xor_sync(0xffffffffu, M0, o));
                M1 = fmaxf(M1, __shfl_xor_sync(0xffffffffu, M1, o));
            }
            const float w0 = exp2f((m0 - M0) * 1.4426950408889634f), w1 = exp2f((m1 - M1) * 1.4426950408889634f);
            float L0 = w0 * dec(d.y), L1 = w1 * dec(d.w);
#pragma unroll
            for (int o = 4; o < 32; o <<= 1) {
                L0 += __shfl_xor_sync(0xffffffffu, L0, o);
                L1 += __shfl_xor_sync(0xffffffffu, L1, o);
            }
            if (g == (c & 7)) *reinterpret_cast<float2*>(sptr + SM_F + t * 8) = make_float2(w0 / L0, w1 / L1);
            bar_arrive(BAR_F, 288);
        } else {
            bar_sync(BAR_INIT, NTHREADS);
        }
        {
            const int hb = warp - 9;
            const unsigned int* po = scr + G_O + ((hb * 4 + (kb >> 3)) * 8 + (kb & 7)) * 1024 + lane * 4;
            uint4 d[8];
            uint32_t pend = 0xffu;
            bar_sync(BAR_O, 384);
            __nanosleep(OG_DELAY);
            for (uint32_t it = 0; it < POLL_LIMIT; it++) {
#pragma unroll
                for (int s = 0; s < 8; s++)
                    if (pend & (1u << s)) d[s] = ld4(po + s * 128);
#pragma unroll
                for (int s = 0; s < 8; s++)
                    if ((pend & (1u << s)) && warp_ok(bad4(d[s], tag))) pend &= ~(1u << s);
                if (pend == 0u) break;
                __nanosleep(100);
            }
            float o0 = 0.f, o1 = 0.f, o2 = 0.f, o3 = 0.f;
#pragma unroll
            for (int s = 0; s < 8; s++) {
                o0 += dec(d[s].x);
                o1 += dec(d[s].y);
                o2 += dec(d[s].z);
                o3 += dec(d[s].w);
            }
            sts64(sbase + SM_OS + hb * FR_STRIDE + lane * 8, pack_bf16(o0, o2), pack_bf16(o1, o3));
            bar_arrive(BAR_OS, 384);
        }
        if (warp != 9) return;
        bar_sync(BAR_B, 288);
        const float bv = bf16r(bf16r(final_sum<8>(scr + G_B + c * 1024, lane, tag, true)) + b2v);
        const float bterm = bf16r(bf16r(1.0f - gate) * bv);
        bar_sync(BAR_A, 288);
        const float aterm = bf16r(gate * bf16r(final_sum<8>(scr + G_A + c * 1024, lane, tag, false)));
        out[(lane >> 3) * D_MODEL + c * 8 + (lane & 7)] = __float2bfloat16_rn(aterm + bterm);
        return;
    }

    bar_sync(BAR_INIT, NTHREADS);

    int stage = 0;
    uint32_t ph = 0;
    const uint32_t l8 = lane & 7;
    const uint32_t rowT = (l8 + 8 * (lane >> 4)) * 128;
    const uint32_t offT = rowT + ((((uint32_t)(2 * mt + ((lane >> 3) & 1))) ^ l8) << 4);
    const bool bvalid = g < 4;
    const int dst_off = ((nb * 32 + warp * 4) * 32 + kb) * 32 + g * 4 + 2 * t;

    {
        float acc0[4] = {0.f, 0.f, 0.f, 0.f}, acc1[4] = {0.f, 0.f, 0.f, 0.f};
        const uint32_t baddr = sbase + SM_XS + (g & 3) * XS_STRIDE + (khalf * 512 + kh2 * 64 + 2 * t) * 2;
#pragma unroll 1
        for (int j = 0; j < 4; j++) {
            mbar_wait(bar_full + stage * 8, ph, flag);
            gemv_tile4(acc0, acc1, sbase + stage * STAGE_BYTES + kh2 * 8192 + offT, baddr + j * 256, bvalid);
            __syncwarp();
            if (lane == 0) mbar_arrive_cnt(bar_empty + stage * 8, 1);
            ++stage;
        }
        float4* red = reinterpret_cast<float4*>(sptr + SM_RED) + mt * 16 + (g * 2 + (t & 1));
        if (kh2 == 1 && t < 2) *red = make_float4(acc0[0] + acc1[0], acc0[1] + acc1[1], acc0[2] + acc1[2], acc0[3] + acc1[3]);
        bar_sync(BAR_PAIR + mt, 64);
        if (kh2 == 0 && t < 2) {
            const float4 o = *red;
            st2(q_dst, enc(acc0[0] + acc1[0] + o.x, tag), enc(acc0[2] + acc1[2] + o.z, tag));
            st2(q_dst + 4096, enc(acc0[1] + acc1[1] + o.y, tag), enc(acc0[3] + acc1[3] + o.w, tag));
        }
    }
    if (has_w1) {
        {
            uint4 xv[4];
#pragma unroll
            for (int i = 0; i < 4; i++) xv[i] = *reinterpret_cast<const uint4*>(sptr + SM_XS + mt * XS_STRIDE + (i * 32 + lane) * 16);
            const uint4 xs = *reinterpret_cast<const uint4*>(sptr + SM_XS + mt * XS_STRIDE + (khalf * 64 + kh2 * 32 + lane) * 16);
            float s0 = 0.f, s1 = 0.f;
#pragma unroll
            for (int i = 0; i < 4; i++) {
                const uint32_t xa[4] = {xv[i].x, xv[i].y, xv[i].z, xv[i].w};
#pragma unroll
                for (int e = 0; e < 4; e++) { s0 += bf_lo(xa[e]); s1 += bf_hi(xa[e]); }
            }
            float s = s0 + s1;
#pragma unroll
            for (int o = 16; o > 0; o >>= 1) s += __shfl_xor_sync(0xffffffffu, s, o);
            const float mean = s * (1.0f / 1024.0f);
            float q0 = 0.f, q1 = 0.f;
#pragma unroll
            for (int i = 0; i < 4; i++) {
                const uint32_t xa[4] = {xv[i].x, xv[i].y, xv[i].z, xv[i].w};
#pragma unroll
                for (int e = 0; e < 4; e++) {
                    const float d0 = bf_lo(xa[e]) - mean, d1 = bf_hi(xa[e]) - mean;
                    q0 = fmaf(d0, d0, q0);
                    q1 = fmaf(d1, d1, q1);
                }
            }
            float q = q0 + q1;
#pragma unroll
            for (int o = 16; o > 0; o >>= 1) q += __shfl_xor_sync(0xffffffffu, q, o);
            const float mb = bf16r(mean);
            const float vb = bf16r(q * (1.0f / 1024.0f));
            const float den = bf16r(sqrtf(bf16r(vb + 1e-5f)));
            const uint32_t xa[4] = {xs.x, xs.y, xs.z, xs.w};
            uint32_t ya[4];
#pragma unroll
            for (int e = 0; e < 4; e++) ya[e] = pack_bf16(bf16r(bf_lo(xa[e]) - mb) / den, bf16r(bf_hi(xa[e]) - mb) / den);
            *reinterpret_cast<uint4*>(sptr + SM_YS + mt * YS_STRIDE + (kh2 * 32 + lane) * 16) = make_uint4(ya[0], ya[1], ya[2], ya[3]);
            bar_sync(BAR_CONS, 256);
        }
        float acc0[4] = {0.f, 0.f, 0.f, 0.f}, acc1[4] = {0.f, 0.f, 0.f, 0.f};
        const uint32_t baddr = sbase + SM_YS + (g & 3) * YS_STRIDE + (kh2 * 64 + 2 * t) * 2;
#pragma unroll 1
        for (int j = 0; j < 4; j++) {
            mbar_wait(bar_full + stage * 8, ph, flag);
            gemv_tile4(acc0, acc1, sbase + stage * STAGE_BYTES + kh2 * 8192 + offT, baddr + j * 256, bvalid);
            __syncwarp();
            if (lane == 0) mbar_arrive_cnt(bar_empty + stage * 8, 1);
            ++stage;
        }
        float4* red = reinterpret_cast<float4*>(sptr + SM_RED + 1024) + mt * 16 + (g * 2 + (t & 1));
        if (kh2 == 1 && t < 2) *red = make_float4(acc0[0] + acc1[0], acc0[1] + acc1[1], acc0[2] + acc1[2], acc0[3] + acc1[3]);
        bar_sync(BAR_PAIR + mt, 64);
        if (kh2 == 0 && t < 2) {
            const float4 o = *red;
            st2(h_dst, enc(acc0[0] + acc1[0] + o.x, tag), enc(acc0[1] + acc1[1] + o.y, tag));
            st2(h_dst + 32, enc(acc0[2] + acc1[2] + o.z, tag), enc(acc0[3] + acc1[3] + o.w, tag));
        }
    } else {
        mbar_wait(bar_full + stage * 8, ph, flag);
    }
    bar_arrive(BAR_W1, 288);
    uint32_t qf[8][2];
    {
        const unsigned int* p = scr + G_Q + (pair >> 2) * 4096 + (pair & 3) * 1024 + tid * 4;
        uint4 d0, d1;
        for (uint32_t it = 0; it < POLL_LIMIT; it++) {
            d0 = ld4(p);
            d1 = ld4(p + 4 * 4096);
            if (warp_ok(bad4(d0, tag) | bad4(d1, tag))) break;
            __nanosleep(200);
        }
        sts64(sbase + SM_QS + warp * FR_STRIDE + lane * 8,
              pack_bf16(dec(d0.x) + dec(d1.x), dec(d0.z) + dec(d1.z)), pack_bf16(dec(d0.y) + dec(d1.y), dec(d0.w) + dec(d1.w)));
        bar_sync(BAR_CONS, 256);
#pragma unroll
        for (int ks = 0; ks < 8; ks++) {
            const uint2 v = lds64(sbase + SM_QS + g * FR_STRIDE + (ks * 4 + t) * 8);
            qf[ks][0] = v.x;
            qf[ks][1] = v.y;
        }
    }
    float sc[8][4];
    {
        int st = stage + kh2;
        uint32_t php = ph;
        const uint32_t krow = mt * 16 + l8 + 8 * ((lane >> 3) & 1);
        const uint32_t khi = lane >> 4;
#pragma unroll
        for (int i = 0; i < 8; i++) {
            mbar_wait(bar_full + st * 8, php, flag);
            const uint32_t base = sbase + st * STAGE_BYTES + krow * 128;
            float c0[4] = {0.f, 0.f, 0.f, 0.f}, c1[4] = {0.f, 0.f, 0.f, 0.f};
            uint32_t a[8][4];
#pragma unroll
            for (int ks = 0; ks < 8; ks++)
                ldsm_x4(a[ks], base + (ks >> 2) * 8192 + (((uint32_t)((ks & 3) * 2) + khi) ^ l8) * 16);
#pragma unroll
            for (int ks = 0; ks < 8; ks++) {
                if (ks & 1) mma16816(c1, a[ks], qf[ks][0], qf[ks][1]);
                else mma16816(c0, a[ks], qf[ks][0], qf[ks][1]);
            }
            __syncwarp();
            if (lane == 0) mbar_arrive_cnt(bar_empty + st * 8, 2);
#pragma unroll
            for (int e = 0; e < 4; e++) sc[i][e] = bf16r(bf16r(c0[e] + c1[e]) * 0.08838834764831845f);
            st += 2;
            if (st >= NSTAGE) { st -= NSTAGE; php ^= 1u; }
        }
        stage += 16 - NSTAGE;
        ph ^= 1u;
        if (stage >= NSTAGE) { stage -= NSTAGE; ph ^= 1u; }
    }
    {
        float m0 = sc[0][0], m1 = sc[0][1];
#pragma unroll
        for (int i = 0; i < 8; i++) {
            m0 = fmaxf(m0, fmaxf(sc[i][0], sc[i][2]));
            m1 = fmaxf(m1, fmaxf(sc[i][1], sc[i][3]));
        }
#pragma unroll
        for (int o = 4; o < 32; o <<= 1) {
            m0 = fmaxf(m0, __shfl_xor_sync(0xffffffffu, m0, o));
            m1 = fmaxf(m1, __shfl_xor_sync(0xffffffffu, m1, o));
        }
        float2* mx = reinterpret_cast<float2*>(sptr + SM_MX);
        if (g == 0) mx[warp * 4 + t] = make_float2(m0, m1);
        bar_sync(BAR_X, 288);
#pragma unroll
        for (int w = 0; w < 8; w++) {
            const float2 v = mx[w * 4 + t];
            m0 = fmaxf(m0, v.x);
            m1 = fmaxf(m1, v.y);
        }
        float l0 = 0.f, l1 = 0.f;
#pragma unroll
        for (int i = 0; i < 8; i++) {
            const float e0 = exp2f((sc[i][0] - m0) * 1.4426950408889634f);
            const float e1 = exp2f((sc[i][1] - m1) * 1.4426950408889634f);
            const float e2 = exp2f((sc[i][2] - m0) * 1.4426950408889634f);
            const float e3 = exp2f((sc[i][3] - m1) * 1.4426950408889634f);
            l0 += e0 + e2;
            l1 += e1 + e3;
            const uint32_t key = (2 * i + kh2) * 64 + mt * 16 + g;
            sts32(sbase + SM_P + key * 16 + t * 4, pack_bf16(e0, e1));
            sts32(sbase + SM_P + (key + 8) * 16 + t * 4, pack_bf16(e2, e3));
        }
#pragma unroll
        for (int o = 4; o < 32; o <<= 1) {
            l0 += __shfl_xor_sync(0xffffffffu, l0, o);
            l1 += __shfl_xor_sync(0xffffffffu, l1, o);
        }
        float2* ls = reinterpret_cast<float2*>(sptr + SM_LS);
        if (g == 0) ls[warp * 4 + t] = make_float2(l0, l1);
        bar_sync(BAR_CONS, 256);
        if (warp == 0) {
            l0 = 0.f;
            l1 = 0.f;
#pragma unroll
            for (int w = 0; w < 8; w++) {
                const float2 v = ls[w * 4 + t];
                l0 += v.x;
                l1 += v.y;
            }
            if (g == 0) st4(scr + G_ML + c * 16 + t * 4, enc(m0, tag), enc(l0, tag), enc(m1, tag), enc(l1, tag));
            bar_arrive(BAR_ML, 64);
        }
    }
    {
        float acc0[4] = {0.f, 0.f, 0.f, 0.f}, acc1[4] = {0.f, 0.f, 0.f, 0.f};
        const uint32_t paddr = sbase + SM_P + lane * 16;
        unsigned int* p = scr + G_O + ((pair * 8 + 2 * t) * 8 + (c & 7)) * 128 + warp * 16 + 2 * g;
#pragma unroll 1
        for (int j = 0; j < 16; j++) {
            if (j == PW_J) {
                st2(p, 0u, 0u);
                st2(p + 1024, 0u, 0u);
                if (t < 2) {
#pragma unroll
                    for (int e = 0; e < 4; e++) {
                        st2(scr + G_A + dst_off + e * 1024, 0u, 0u);
                        st2(scr + G_B + dst_off + e * 1024, 0u, 0u);
                    }
                }
            }
            uint32_t pb[2][4];
            ldsm_x4_t(pb[0], paddr + j * 1024);
            ldsm_x4_t(pb[1], paddr + j * 1024 + 512);
            mbar_wait(bar_full + stage * 8, ph, flag);
            const uint32_t base = sbase + stage * STAGE_BYTES + kh2 * 8192 + offT;
            uint32_t a[4][4];
#pragma unroll
            for (int ks = 0; ks < 4; ks++) ldsm_x4_t(a[ks], base + ks * 2048);
            mma16816(acc0, a[0], pb[0][0], pb[0][1]);
            mma16816(acc1, a[1], pb[0][2], pb[0][3]);
            mma16816(acc0, a[2], pb[1][0], pb[1][1]);
            mma16816(acc1, a[3], pb[1][2], pb[1][3]);
            __syncwarp();
            if (lane == 0) mbar_arrive_cnt(bar_empty + stage * 8, 1);
            if (++stage == NSTAGE) { stage = 0; ph ^= 1u; }
            if (j == 14) bar_sync(BAR_F, 288);
        }
        const float2 f = *reinterpret_cast<const float2*>(sptr + SM_F + t * 8);
        st2(p, enc((acc0[0] + acc1[0]) * f.x, tag), enc((acc0[2] + acc1[2]) * f.x, tag));
        st2(p + 1024, enc((acc0[1] + acc1[1]) * f.y, tag), enc((acc0[3] + acc1[3]) * f.y, tag));
        bar_arrive(BAR_O, 384);
    }
    const uint32_t offW0 = (warp >> 1) * 2048 + rowT + ((((uint32_t)(4 * (warp & 1) + ((lane >> 3) & 1))) ^ l8) << 4);
    const uint32_t offW1 = (warp >> 1) * 2048 + rowT + ((((uint32_t)(4 * (warp & 1) + 2 + ((lane >> 3) & 1))) ^ l8) << 4);
    {
        bar_sync(BAR_HS, 288);
        float acc0[4] = {0.f, 0.f, 0.f, 0.f}, acc1[4] = {0.f, 0.f, 0.f, 0.f};
        const uint32_t baddr = sbase + SM_HS + (g & 3) * HS_STRIDE + t * 4;
#pragma unroll 1
        for (int j = 0; j < 3; j++) {
            uint32_t b[4] = {0u, 0u, 0u, 0u};
            if (bvalid) {
#pragma unroll
                for (int e = 0; e < 4; e++) b[e] = lds32(baddr + j * 64 + e * 16);
            }
            mbar_wait(bar_full + stage * 8, ph, flag);
            const uint32_t base = sbase + stage * STAGE_BYTES;
            uint32_t a[4][4];
            ldsm_x4_t(a[0], base + offW0);
            ldsm_x4_t(a[1], base + offW1);
            ldsm_x4_t(a[2], base + 8192 + offW0);
            ldsm_x4_t(a[3], base + 8192 + offW1);
            mma16816(acc0, a[0], b[0], b[1]);
            mma16816(acc1, a[1], b[0], b[1]);
            mma16816(acc0, a[2], b[2], b[3]);
            mma16816(acc1, a[3], b[2], b[3]);
            ++stage;
        }
        {
            uint32_t b0 = 0u, b1_ = 0u;
            if (bvalid) { b0 = lds32(baddr + 192); b1_ = lds32(baddr + 208); }
            mbar_wait(bar_full + stage * 8, ph, flag);
            const uint32_t base = sbase + stage * STAGE_BYTES;
            uint32_t a[2][4];
            ldsm_x4_t(a[0], base + offW0);
            ldsm_x4_t(a[1], base + offW1);
            mma16816(acc0, a[0], b0, b1_);
            mma16816(acc1, a[1], b0, b1_);
            ++stage;
        }
        if (t < 2) {
            unsigned int* p = scr + G_B + dst_off;
            st2(p, enc(acc0[0], tag), enc(acc0[1], tag));
            st2(p + 1024, enc(acc0[2], tag), enc(acc0[3], tag));
            st2(p + 2048, enc(acc1[0], tag), enc(acc1[1], tag));
            st2(p + 3072, enc(acc1[2], tag), enc(acc1[3], tag));
        }
        bar_arrive(BAR_B, 288);
    }
    {
        bar_sync(BAR_OS, 384);
        float acc0[4] = {0.f, 0.f, 0.f, 0.f}, acc1[4] = {0.f, 0.f, 0.f, 0.f};
        const uint32_t baddr = sbase + SM_OS + (g & 3) * FR_STRIDE + t * 8;
#pragma unroll 1
        for (int j = 0; j < 4; j++) {
            uint2 b0 = make_uint2(0u, 0u), b1_ = make_uint2(0u, 0u);
            if (bvalid) { b0 = lds64(baddr + j * 64); b1_ = lds64(baddr + j * 64 + 32); }
            mbar_wait(bar_full + stage * 8, ph, flag);
            const uint32_t base = sbase + stage * STAGE_BYTES;
            uint32_t a[4][4];
            ldsm_x4_t(a[0], base + offW0);
            ldsm_x4_t(a[1], base + offW1);
            ldsm_x4_t(a[2], base + 8192 + offW0);
            ldsm_x4_t(a[3], base + 8192 + offW1);
            mma16816(acc0, a[0], b0.x, b0.y);
            mma16816(acc1, a[1], b0.x, b0.y);
            mma16816(acc0, a[2], b1_.x, b1_.y);
            mma16816(acc1, a[3], b1_.x, b1_.y);
            ++stage;
        }
        if (t < 2) {
            unsigned int* p = scr + G_A + dst_off;
            st2(p, enc(acc0[0], tag), enc(acc0[1], tag));
            st2(p + 1024, enc(acc0[2], tag), enc(acc0[3], tag));
            st2(p + 2048, enc(acc1[0], tag), enc(acc1[1], tag));
            st2(p + 3072, enc(acc1[2], tag), enc(acc1[3], tag));
        }
    }
    bar_arrive(BAR_A, 288);
}

}

namespace c6 {

constexpr int CS = 6;
constexpr int NCL = 16;
constexpr int NCTA = NCL * CS;
constexpr int NTHREADS = 416;
constexpr int NST = 11;

constexpr int SM_P = NST * STAGE_BYTES;
constexpr int SM_XS = SM_P;
constexpr int SM_YS = SM_P + 8256;
constexpr int SM_OS = SM_P;
constexpr int SM_QS = SM_P + 22528;
constexpr int SM_HS = SM_QS + 2304;
constexpr int SM_RED = SM_HS + 5248;
constexpr int SM_MX = SM_RED + 2048;
constexpr int SM_LS = SM_MX + 256;
constexpr int SM_F = SM_LS + 256;
constexpr int SM_G = SM_F + 32;
constexpr int SM_ST = SM_G + 16;
constexpr int SM_OR = SM_ST + 384;
constexpr int SM_XR = SM_OR + 6144;
constexpr int SM_BAR = SM_XR + 6144;
constexpr int SM_FLAG = SM_BAR + (2 * NST + 5) * 8;
constexpr int SM_TOTAL = SM_FLAG + 8;
constexpr int SM_ALLOC = SM_TOTAL + 1024;
constexpr int HS_STRIDE = 1312;
constexpr int OS_STRIDE = 1568;
constexpr int BAR_Y = BAR_X;
constexpr int BAR_HELP = BAR_ML;

#define PRE_OUT 0
#define CAP6 5
#define LEAD6 3
#define OG_GAP 100
#define OG6_DELAY 300
#define PT6 660
constexpr uint32_t P_B = PT6 * 192;
#define PACE_L PT6
constexpr uint32_t P_L = PACE_L * 192;
constexpr uint32_t P_52 = (uint32_t)((long long)P_B * (316 - 6 * LEAD6) / (6 * (52 - LEAD6)));
constexpr uint32_t P_54 = (uint32_t)((long long)P_B * (316 - 6 * LEAD6) / (6 * (54 - LEAD6)));
#define OFF6 400

constexpr int G_EPOCH = 0;
constexpr int G_Q = G_EPOCH + 128 * 4;
constexpr int G_H = G_Q + 2 * 4 * 4096;
constexpr int G_O = G_H + 2 * 4 * 4096;
constexpr int G_TOTAL = G_O + 4 * 4096;
__device__ __align__(1024) unsigned int g_scratch[G_TOTAL];

#define KTW(w, i)
#define KTA(i)

__device__ __forceinline__ void load_b(uint2 (&b)[4], uint32_t b_addr, bool bvalid) {
#pragma unroll
    for (int ks = 0; ks < 4; ks++) b[ks] = bvalid ? lds64(b_addr + ks * 32) : make_uint2(0u, 0u);
}
__device__ __forceinline__ void st_async2(uint32_t addr, float a, float b, uint32_t bar) {
    asm volatile("st.async.weak.shared::cluster.mbarrier::complete_tx::bytes.v2.f32 [%0], {%1, %2}, [%3];"
                 ::"r"(addr), "f"(a), "f"(b), "r"(bar) : "memory");
}
__device__ __forceinline__ void st_async4(uint32_t addr, float a, float b, float c, float d, uint32_t bar) {
    asm volatile("st.async.weak.shared::cluster.mbarrier::complete_tx::bytes.v4.f32 [%0], {%1, %2, %3, %4}, [%5];"
                 ::"r"(addr), "f"(a), "f"(b), "f"(c), "f"(d), "r"(bar) : "memory");
}
__device__ __forceinline__ uint32_t mapa(uint32_t addr, uint32_t rank) {
    uint32_t r;
    asm volatile("mapa.shared::cluster.u32 %0, %1, %2;" : "=r"(r) : "r"(addr), "r"(rank));
    return r;
}

__global__ void __launch_bounds__(NTHREADS, 1)
fused_kernel(const __nv_bfloat16* __restrict__ wq, const __nv_bfloat16* __restrict__ x, unsigned int* __restrict__ scr,
             __nv_bfloat16* __restrict__ out, const __nv_bfloat16* __restrict__ gate_w, const __nv_bfloat16* __restrict__ b1,
             const __grid_constant__ TMaps maps, const __nv_bfloat16* __restrict__ b2) {
    extern __shared__ unsigned char smem_raw[];
    const uint32_t sbase = (smem_u32(smem_raw) + 1023u) & ~1023u;
    unsigned char* sptr = smem_raw + (sbase - smem_u32(smem_raw));
    volatile uint32_t* flag = reinterpret_cast<volatile uint32_t*>(sptr + SM_FLAG);

    const int c = blockIdx.x;
    const int tid = threadIdx.x;
    const int warp = tid >> 5;
    const int lane = tid & 31;
    const int cl = c / CS, r = c - cl * CS;
    const int u0 = 8 * cl + (r < 2 ? 2 * r : r + 2);
    const int v0 = 7 * cl + 2 * (r - 2);
    const int nblk = 22 - ((0x0021100 >> (4 * r)) & 3);
    const int n2 = r < 4 ? 5 : 4;
    const int w2_0 = min(5 * r, 24), wo_0 = 5 * r + (r == 5);
    const uint32_t bar_full = sbase + SM_BAR;
    const uint32_t bar_empty = sbase + SM_BAR + NST * 8;
    const uint32_t bar_st = sbase + SM_BAR + 2 * NST * 8;
    const uint32_t bar_or = bar_st + 8;
    const uint32_t bar_xr = bar_st + 24;

    KTW(0, 0);
    if (warp == 8) {
        uint32_t t0 = 0;
        if (lane == 0) {
#pragma unroll
            for (int j = 0; j < LEAD6; j++) mbar_init(bar_full + j * 8, 1);
            asm volatile("fence.mbarrier_init.release.cluster;" ::: "memory");
            asm volatile("fence.proxy.async.shared::cta;" ::: "memory");
#pragma unroll
            for (int j = 0; j < LEAD6; j++) {
                mbar_expect_tx(bar_full + j * 8, STAGE_BYTES);
                tma_3d(sbase + j * STAGE_BYTES, &maps.wq3, 0, (u0 & 1) * 512 + j * 128, u0 >> 1, bar_full + j * 8);
            }
            t0 = gtime32() + OFF6 + (r * NCL + cl) * PT6 / 128;
#pragma unroll
            for (int i = LEAD6; i < NST; i++) mbar_init(bar_full + i * 8, 1);
#pragma unroll
            for (int i = 0; i < NST; i++) mbar_init(bar_empty + i * 8, 8);
#pragma unroll
            for (int i = 0; i < 5; i++) {
                mbar_init(bar_st + i * 8, 1);
                mbar_expect_tx(bar_st + i * 8, i == 0 ? 384 : 3072);
            }
            *flag = 0u;
            asm volatile("fence.mbarrier_init.release.cluster;" ::: "memory");
            asm volatile("fence.proxy.async.shared::cta;" ::: "memory");
            prefetch_tmap(&maps.w1n);
            prefetch_tmap(&maps.k);
            prefetch_tmap(&maps.v);
            prefetch_tmap(&maps.w2n);
            prefetch_tmap(&maps.won);
        }
        __syncwarp();
        asm volatile("barrier.cluster.arrive.relaxed.aligned;" ::: "memory");
        bar_arrive(BAR_INIT, NTHREADS);
        if (lane == 0) {
            const int kv_row0 = cl * SK + r * 64;
            uint32_t fb = bar_full + LEAD6 * 8, eph = 1u;
            uint32_t lb = bar_full + (LEAD6 + NST - CAP6) % NST * 8, lph = 1u;
            uint32_t due = t0 << 8;
#pragma unroll 1
            for (int phase = 0; phase < 7; phase++) {
                const CUtensorMap* map;
                int row, drow = 128, blk, n;
                uint32_t per = (r == 2 || r == 3) ? P_54 : P_52;
                if (phase == 0) {
                    map = &maps.wq3; row = (u0 & 1) * 512 + LEAD6 * 128; blk = u0 >> 1; n = 4 - LEAD6;
                } else if (phase < 3) {
                    const int unit = r < 2 ? u0 + 1 : v0 + phase - 1;
                    map = r < 2 ? &maps.wq3 : &maps.w1n; row = (unit & 1) * 512; blk = unit >> 1;
                    n = (phase == 2 && (r < 2 || r == 5)) ? 0 : 4;
                } else if (phase < 5) {
                    map = phase == 3 ? &maps.k : &maps.v; row = kv_row0; drow = 384; blk = 0; n = nblk;
                } else {
                    map = phase == 5 ? &maps.w2n : &maps.won; row = (phase == 5 ? w2_0 : wo_0) * 128; blk = cl;
                    n = phase == 5 ? n2 : 10 - n2; per = P_L;
                }
#pragma unroll 1
                for (int j = 0; j < n; j++) {
                    const uint32_t dst = sbase + (fb - bar_full) * (STAGE_BYTES / 8);
                    mbar_wait(lb, lph, flag);
                    mbar_wait(fb + NST * 8, eph, flag);
                    mbar_expect_tx(fb, STAGE_BYTES);
                    for (int it = 0; it < 100000 && (int)((gtime32() << 8) - due) < 0; it++) {}
                    tma_3d(dst, map, 0, row, blk, fb);
                    row += drow;
                    if (j == 20 && r == 5) row -= 7 * 64;
                    due += per;
                    fb += 8;
                    if (fb == bar_empty) { fb = bar_full; eph ^= 1u; }
                    lb += 8;
                    if (lb == bar_empty) { lb = bar_full; lph ^= 1u; }
                }
            }
            KTW(8, 13);
        }
        return;
    }
    asm volatile("barrier.cluster.arrive.relaxed.aligned;" ::: "memory");

    const int g = lane >> 2;
    const int t = lane & 3;
    const int mt = warp & 3;
    const int kh2 = warp >> 2;
    const uint32_t epoch = ld1(scr + G_EPOCH + c * 4) + 1u;
    asm volatile("prefetch.global.L2 [%0];" ::"l"(wq + (size_t)((u0 & 1) * 512 + (tid < 256 ? tid : tid - 32)) * 4096 + (u0 >> 1) * 64));
    const uint32_t tag = 1u + epoch % 3u;

    if (warp >= 9) {
        const int hb = warp - 9;
        const bool fin = r < 4 && hb < 2;
        const int col = cl * 64 + r * 16 + hb * 8 + (lane & 7);
        float b2v = 0.f;
        {
            uint4 xv[4], gw[4];
#pragma unroll
            for (int i = 0; i < 4; i++) xv[i] = __ldg(reinterpret_cast<const uint4*>(x) + hb * 128 + i * 32 + lane);
#pragma unroll
            for (int i = 0; i < 4; i++) gw[i] = __ldg(reinterpret_cast<const uint4*>(gate_w) + i * 32 + lane);
            if (fin) b2v = __bfloat162float(b2[col]);
            bar_sync(BAR_INIT, NTHREADS);
            float s0 = 0.f, s1 = 0.f, zs = 0.f;
#pragma unroll
            for (int i = 0; i < 4; i++) {
                const uint32_t xa[4] = {xv[i].x, xv[i].y, xv[i].z, xv[i].w};
                const uint32_t wa[4] = {gw[i].x, gw[i].y, gw[i].z, gw[i].w};
#pragma unroll
                for (int e = 0; e < 4; e++) {
                    s0 += bf_lo(xa[e]);
                    s1 += bf_hi(xa[e]);
                    zs += bf16r(bf_lo(xa[e]) * bf_lo(wa[e]));
                    zs += bf16r(bf_hi(xa[e]) * bf_hi(wa[e]));
                }
            }
            float s = s0 + s1;
#pragma unroll
            for (int o = 16; o > 0; o >>= 1) {
                s += __shfl_xor_sync(0xffffffffu, s, o);
                zs += __shfl_xor_sync(0xffffffffu, zs, o);
            }
            if (r >= 2) {
                const float mean = s * (1.0f / 1024.0f);
                float q0 = 0.f, q1 = 0.f;
#pragma unroll
                for (int i = 0; i < 4; i++) {
                    const uint32_t xa[4] = {xv[i].x, xv[i].y, xv[i].z, xv[i].w};
#pragma unroll
                    for (int e = 0; e < 4; e++) {
                        const float d0 = bf_lo(xa[e]) - mean, d1 = bf_hi(xa[e]) - mean;
                        q0 = fmaf(d0, d0, q0);
                        q1 = fmaf(d1, d1, q1);
                    }
                }
                float q = q0 + q1;
#pragma unroll
                for (int o = 16; o > 0; o >>= 1) q += __shfl_xor_sync(0xffffffffu, q, o);
                const float mb = bf16r(mean);
                const float vb = bf16r(q * (1.0f / 1024.0f));
                const float den = bf16r(sqrtf(bf16r(vb + 1e-5f)));
#pragma unroll
                for (int i = 0; i < 4; i++) {
                    const uint32_t xa[4] = {xv[i].x, xv[i].y, xv[i].z, xv[i].w};
                    uint32_t ya[4];
#pragma unroll
                    for (int e = 0; e < 4; e++) ya[e] = pack_bf16(bf16r(bf_lo(xa[e]) - mb) / den, bf16r(bf_hi(xa[e]) - mb) / den);
                    *reinterpret_cast<uint4*>(sptr + SM_YS + hb * XS_STRIDE + (i * 32 + lane) * 16) = make_uint4(ya[0], ya[1], ya[2], ya[3]);
                }
                bar_arrive(BAR_Y, 384);
            }
            zs = bf16r(zs);
            if (lane == 0) reinterpret_cast<float*>(sptr + SM_G)[hb] = bf16r(1.0f / (1.0f + __expf(-zs)));
        }
        const int sl = r + 6 * (hb - 2);
        const bool red_o = hb >= 2 && sl < 8;
        unsigned int* const o_dst = scr + G_O + cl * 1024 + g * 128 + sl * 16 + t * 4;
        bar_sync(BAR_HELP, 160);
        if (red_o) st4(o_dst, 0u, 0u, 0u, 0u);
        if (hb == 3) {
            mbar_wait_cluster(bar_st, flag);
            float4 d = make_float4(-INFINITY, 0.f, -INFINITY, 0.f);
            if (g < CS) d = *reinterpret_cast<const float4*>(sptr + SM_ST + lane * 16);
            float M0 = d.x, M1 = d.z;
#pragma unroll
            for (int o = 4; o < 32; o <<= 1) {
                M0 = fmaxf(M0, __shfl_xor_sync(0xffffffffu, M0, o));
                M1 = fmaxf(M1, __shfl_xor_sync(0xffffffffu, M1, o));
            }
            const float w0 = exp2f((d.x - M0) * 1.4426950408889634f), w1 = exp2f((d.z - M1) * 1.4426950408889634f);
            float L0 = w0 * d.y, L1 = w1 * d.w;
#pragma unroll
            for (int o = 4; o < 32; o <<= 1) {
                L0 += __shfl_xor_sync(0xffffffffu, L0, o);
                L1 += __shfl_xor_sync(0xffffffffu, L1, o);
            }
            if (g == r) *reinterpret_cast<float2*>(sptr + SM_F + t * 8) = make_float2(w0 / L0, w1 / L1);
            bar_arrive(BAR_F, 288);
        }
        {
            const unsigned int* p = scr + G_H + hb * 4096 + w2_0 * 128 + lane * 4;
            const uint32_t* pb = reinterpret_cast<const uint32_t*>(b1 + w2_0 * 128 + g * 16 + 2 * t);
#pragma unroll 1
            for (int i = 0; i < n2; i++) {
                const uint32_t ba = __ldg(pb + i * 64), bb = __ldg(pb + i * 64 + 4);
                uint4 d0, d1;
                for (uint32_t it = 0; it < POLL_LIMIT; it++) {
                    d0 = ld4(p + i * 128);
                    d1 = ld4(p + i * 128 + 4 * 4096);
                    if (warp_ok(bad4(d0, tag) | bad4(d1, tag))) break;
                    __nanosleep(200);
                }
                const float sv[4] = {dec(d0.x) + dec(d1.x), dec(d0.z) + dec(d1.z), dec(d0.y) + dec(d1.y), dec(d0.w) + dec(d1.w)};
                const float bv[4] = {bf_lo(ba), bf_hi(ba), bf_lo(bb), bf_hi(bb)};
                float h[4];
#pragma unroll
                for (int e = 0; e < 4; e++) {
                    const float v = bf16r(bf16r(sv[e]) + bv[e]);
                    const float inner = 0.7978845608028654f * (v + 0.044715f * v * v * v);
                    h[e] = 0.5f * v * (1.0f + tanhf(inner));
                }
                sts64(sbase + SM_HS + hb * HS_STRIDE + i * 256 + lane * 8, pack_bf16(h[0], h[1]), pack_bf16(h[2], h[3]));
            }
            KTW(9, 7);
            bar_arrive(BAR_HS, 384);
        }
        const float gate = reinterpret_cast<const float*>(sptr + SM_G)[lane >> 3];
        bar_sync(BAR_O, 384);
        if (red_o) {
            const float4* po = reinterpret_cast<const float4*>(sptr + SM_OR + (hb - 2) * 3072) + lane;
            mbar_wait_cluster(bar_or + (hb - 2) * 8, flag);
            float4 v[CS];
#pragma unroll
            for (int s = 0; s < CS; s++) v[s] = po[s * 32];
            const float o0 = ((v[0].x + v[1].x) + (v[2].x + v[3].x)) + (v[4].x + v[5].x);
            const float o1 = ((v[0].y + v[1].y) + (v[2].y + v[3].y)) + (v[4].y + v[5].y);
            const float o2 = ((v[0].z + v[1].z) + (v[2].z + v[3].z)) + (v[4].z + v[5].z);
            const float o3 = ((v[0].w + v[1].w) + (v[2].w + v[3].w)) + (v[4].w + v[5].w);
            st4(o_dst, __float_as_uint(bf16r(o0)) | tag, __float_as_uint(bf16r(o1)) | tag, __float_as_uint(bf16r(o2)) | tag,
                __float_as_uint(bf16r(o3)) | tag);
            KTW(11, 28);
        }
        __nanosleep(OG6_DELAY);
        {
            const unsigned int* po = scr + G_O + hb * 4096 + wo_0 * 128 + lane * 4;
            uint4 d[6];
            uint32_t pend = r < 4 ? 0x1fu : 0x3fu;
            for (uint32_t it = 0; it < POLL_LIMIT; it++) {
#pragma unroll
                for (int s = 0; s < 6; s++)
                    if (pend & (1u << s)) d[s] = ld4(po + s * 128);
#pragma unroll
                for (int s = 0; s < 6; s++) {
                    if ((pend & (1u << s)) && warp_ok(bad4(d[s], tag))) {
                        pend &= ~(1u << s);
                        sts64(sbase + SM_OS + hb * OS_STRIDE + s * 256 + lane * 8, __byte_perm(d[s].x, d[s].z, 0x7632),
                              __byte_perm(d[s].y, d[s].w, 0x7632));
                    }
                }
                if (pend == 0u) {
                    break;
                }
                __nanosleep(OG_GAP);
            }
            KTA(15);
            bar_arrive(BAR_OS, 384);
        }
        if (fin) {
            const float gm = bf16r(1.0f - gate);
            float term[2];
#pragma unroll
            for (int br = 0; br < 2; br++) {
                const float* xr = reinterpret_cast<const float*>(sptr + SM_XR) + br * 768 + hb * 32 + (lane & 7) * 4 + (lane >> 3);
                mbar_wait_cluster(bar_xr + br * 8, flag);
                KTW(9, 10 + br);
                float v[12];
#pragma unroll
                for (int s = 0; s < 12; s++) v[s] = xr[s * 64];
#pragma unroll
                for (int s = 0; s < 6; s++) v[s] += v[s + 6];
                const float sum = bf16r(((v[0] + v[1]) + (v[2] + v[3])) + (v[4] + v[5]));
                term[br] = br == 0 ? bf16r(gm * bf16r(sum + b2v)) : bf16r(gate * sum);
            }
            out[(lane >> 3) * D_MODEL + col] = __float2bfloat16_rn(term[1] + term[0]);
        }
        KTW(9, 12);
        return;
    }

    {
        const uint4 x0 = __ldg(reinterpret_cast<const uint4*>(x) + tid);
        const uint4 x1 = __ldg(reinterpret_cast<const uint4*>(x) + 256 + tid);
        if (t < 2 && (kh2 == 0 || r < 2)) {
            unsigned int* const q_dst = scr + G_Q + (((u0 + kh2) & 1) * 4 + 2 * t) * 4096 + (u0 >> 1) * 64 + mt * 16 + 2 * g;
            st2(q_dst, 0u, 0u);
            st2(q_dst + 4096, 0u, 0u);
        }
        *reinterpret_cast<uint4*>(sptr + SM_XS + (tid >> 7) * XS_STRIDE + (tid & 127) * 16) = x0;
        *reinterpret_cast<uint4*>(sptr + SM_XS + (2 + (tid >> 7)) * XS_STRIDE + (tid & 127) * 16) = x1;
    }
    bar_sync(BAR_INIT, NTHREADS);

    int stage = 0;
    uint32_t ph = 0;
    const uint32_t l8 = lane & 7;
    const uint32_t rowT = (l8 + 8 * (lane >> 4)) * 128;
    const uint32_t offT = rowT + ((((uint32_t)(2 * mt + ((lane >> 3) & 1))) ^ l8) << 4);
    const uint32_t aoff = sbase + kh2 * 8192 + offT;
    const bool bvalid = g < 4;

#pragma unroll 1
    for (int ui = 0; ui < ((r >= 2 && r <= 4) ? 3 : 2); ui++) {
        const bool isq = ui == 0 || r < 2;
        const int unit = isq ? u0 + ui : v0 + ui - 1;
        float4* const red = reinterpret_cast<float4*>(sptr + SM_RED) + (ui & 1) * 64 + mt * 16 + (g * 2 + (t & 1));
        unsigned int* const dst = scr + (isq ? G_Q : G_H) + ((unit & 1) * 4 + 2 * t) * 4096 + (unit >> 1) * 64 + mt * 16 + 2 * g;
        float acc0[4] = {0.f, 0.f, 0.f, 0.f}, acc1[4] = {0.f, 0.f, 0.f, 0.f};
        const uint32_t baddr = sbase + (isq ? SM_XS : SM_YS) + (g & 3) * XS_STRIDE + ((unit & 1) * 512 + kh2 * 64 + 2 * t) * 2;
        if (ui == 1 && r >= 2) bar_sync(BAR_Y, 384);
#pragma unroll 1
        for (int j = 0; j < 4; j++) {
            mbar_wait(bar_full + stage * 8, ph, flag);
            gemv_tile4(acc0, acc1, aoff + stage * STAGE_BYTES, baddr + j * 256, bvalid);
            __syncwarp();
            if (lane == 0) mbar_arrive_cnt(bar_empty + stage * 8, 1);
            if (++stage == NST) { stage = 0; ph ^= 1u; }
        }
        if (kh2 == 1 && t < 2) *red = make_float4(acc0[0] + acc1[0], acc0[1] + acc1[1], acc0[2] + acc1[2], acc0[3] + acc1[3]);
        bar_sync(BAR_PAIR + mt, 64);
        if (kh2 == 0 && t < 2) {
            const float4 o = *red;
            st2(dst, enc(acc0[0] + acc1[0] + o.x, tag), enc(acc0[2] + acc1[2] + o.z, tag));
            st2(dst + 4096, enc(acc0[1] + acc1[1] + o.y, tag), enc(acc0[3] + acc1[3] + o.w, tag));
        }
    }
    KTW(0, 1);
    mbar_wait(bar_full + stage * 8, ph, flag);
    uint32_t qf[8][2];
    {
        const unsigned int* p = scr + G_Q + cl * 1024 + tid * 4;
        uint4 d0, d1;
        for (uint32_t it = 0; it < POLL_LIMIT; it++) {
            d0 = ld4(p);
            d1 = ld4(p + 4 * 4096);
            if (warp_ok(bad4(d0, tag) | bad4(d1, tag))) break;
            __nanosleep(200);
        }
        sts64(sbase + SM_QS + warp * FR_STRIDE + lane * 8,
              pack_bf16(dec(d0.x) + dec(d1.x), dec(d0.z) + dec(d1.z)), pack_bf16(dec(d0.y) + dec(d1.y), dec(d0.w) + dec(d1.w)));
        bar_sync(BAR_CONS, 256);
#pragma unroll
        for (int ks = 0; ks < 8; ks++) {
            const uint2 v = lds64(sbase + SM_QS + g * FR_STRIDE + (ks * 4 + t) * 8);
            qf[ks][0] = v.x;
            qf[ks][1] = v.y;
        }
    }
    KTW(0, 2);
    {
        float sc[11][4];
        const bool full = nblk - kh2 >= 21;
        {
            int st = stage + kh2;
            uint32_t php = ph;
            if (st >= NST) { st -= NST; php ^= 1u; }
            const uint32_t krow = mt * 16 + l8 + 8 * ((lane >> 3) & 1);
            const uint32_t khi = lane >> 4;
#pragma unroll
            for (int i = 0; i < 11; i++) {
                if (i < 10 || full) {
                    mbar_wait(bar_full + st * 8, php, flag);
                    const uint32_t base = sbase + st * STAGE_BYTES + krow * 128;
                    float c0[4] = {0.f, 0.f, 0.f, 0.f}, c1[4] = {0.f, 0.f, 0.f, 0.f};
                    uint32_t a[8][4];
#pragma unroll
                    for (int ks = 0; ks < 8; ks++)
                        ldsm_x4(a[ks], base + (ks >> 2) * 8192 + (((uint32_t)((ks & 3) * 2) + khi) ^ l8) * 16);
#pragma unroll
                    for (int ks = 0; ks < 8; ks++) {
                        if (ks & 1) mma16816(c1, a[ks], qf[ks][0], qf[ks][1]);
                        else mma16816(c0, a[ks], qf[ks][0], qf[ks][1]);
                    }
                    __syncwarp();
                    if (lane == 0) mbar_arrive_cnt(bar_empty + st * 8, 2);
#pragma unroll
                    for (int e = 0; e < 4; e++) sc[i][e] = bf16r(bf16r(c0[e] + c1[e]) * 0.08838834764831845f);
                    st += 2;
                    if (st >= NST) { st -= NST; php ^= 1u; }
                } else {
#pragma unroll
                    for (int e = 0; e < 4; e++) sc[i][e] = sc[0][e];
                }
            }
            stage += nblk - NST;
            ph ^= 1u;
            if (stage >= NST) { stage -= NST; ph ^= 1u; }
        }
        KTW(0, 3);
        float m0 = sc[0][0], m1 = sc[0][1];
#pragma unroll
        for (int i = 0; i < 11; i++) {
            m0 = fmaxf(m0, fmaxf(sc[i][0], sc[i][2]));
            m1 = fmaxf(m1, fmaxf(sc[i][1], sc[i][3]));
        }
#pragma unroll
        for (int o = 4; o < 32; o <<= 1) {
            m0 = fmaxf(m0, __shfl_xor_sync(0xffffffffu, m0, o));
            m1 = fmaxf(m1, __shfl_xor_sync(0xffffffffu, m1, o));
        }
        float2* mx = reinterpret_cast<float2*>(sptr + SM_MX);
        if (g == 0) mx[warp * 4 + t] = make_float2(m0, m1);
        bar_sync(BAR_CONS, 256);
#pragma unroll
        for (int w = 0; w < 8; w++) {
            const float2 v = mx[w * 4 + t];
            m0 = fmaxf(m0, v.x);
            m1 = fmaxf(m1, v.y);
        }
        float l0 = 0.f, l1 = 0.f;
#pragma unroll
        for (int i = 0; i < 11; i++) {
            if (i < 10 || full) {
                const float e0 = exp2f((sc[i][0] - m0) * 1.4426950408889634f);
                const float e1 = exp2f((sc[i][1] - m1) * 1.4426950408889634f);
                const float e2 = exp2f((sc[i][2] - m0) * 1.4426950408889634f);
                const float e3 = exp2f((sc[i][3] - m1) * 1.4426950408889634f);
                l0 += e0 + e2;
                l1 += e1 + e3;
                const uint32_t key = (2 * i + kh2) * 64 + mt * 16 + g;
                sts32(sbase + SM_P + key * 16 + t * 4, pack_bf16(e0, e1));
                sts32(sbase + SM_P + (key + 8) * 16 + t * 4, pack_bf16(e2, e3));
            }
        }
#pragma unroll
        for (int o = 4; o < 32; o <<= 1) {
            l0 += __shfl_xor_sync(0xffffffffu, l0, o);
            l1 += __shfl_xor_sync(0xffffffffu, l1, o);
        }
        float2* ls = reinterpret_cast<float2*>(sptr + SM_LS);
        if (g == 0) ls[warp * 4 + t] = make_float2(l0, l1);
        bar_sync(BAR_CONS, 256);
        asm volatile("barrier.cluster.wait.acquire.aligned;" ::: "memory");
        if (warp == 0) {
            l0 = 0.f;
            l1 = 0.f;
#pragma unroll
            for (int w = 0; w < 8; w++) {
                const float2 v = ls[w * 4 + t];
                l0 += v.x;
                l1 += v.y;
            }
            if (g < CS) st_async4(mapa(sbase + SM_ST + r * 64 + t * 16, g), m0, l0, m1, l1, mapa(bar_st, g));
            bar_arrive(BAR_HELP, 160);
        }
    }
    {
        float acc0[4] = {0.f, 0.f, 0.f, 0.f}, acc1[4] = {0.f, 0.f, 0.f, 0.f};
        const uint32_t paddr = sbase + SM_P + lane * 16;
        const uint32_t sel = warp >= CS ? 1u : 0u;
        const uint32_t ro = mapa(sbase + SM_OR + sel * 3072 + r * 512 + t * 128 + g * 8, warp - sel * CS);
        const uint32_t rb = mapa(bar_or + sel * 8, warp - sel * CS);
#pragma unroll 1
        for (int j = 0; j < nblk; j++) {
            uint32_t pb[2][4];
            ldsm_x4_t(pb[0], paddr + j * 1024);
            ldsm_x4_t(pb[1], paddr + j * 1024 + 512);
            mbar_wait(bar_full + stage * 8, ph, flag);
            const uint32_t base = aoff + stage * STAGE_BYTES;
            uint32_t a[4][4];
#pragma unroll
            for (int ks = 0; ks < 4; ks++) ldsm_x4_t(a[ks], base + ks * 2048);
            mma16816(acc0, a[0], pb[0][0], pb[0][1]);
            mma16816(acc1, a[1], pb[0][2], pb[0][3]);
            mma16816(acc0, a[2], pb[1][0], pb[1][1]);
            mma16816(acc1, a[3], pb[1][2], pb[1][3]);
            __syncwarp();
            if (lane == 0) mbar_arrive_cnt(bar_empty + stage * 8, 1);
            if (++stage == NST) { stage = 0; ph ^= 1u; }
            if (j == nblk - 2) {
                bar_sync(BAR_F, 288);
                bar_sync(BAR_HS, 384);
            }
        }
        const float2 f = *reinterpret_cast<const float2*>(sptr + SM_F + t * 8);
        st_async2(ro, (acc0[0] + acc1[0]) * f.x, (acc0[2] + acc1[2]) * f.x, rb);
        st_async2(ro + 64, (acc0[1] + acc1[1]) * f.y, (acc0[3] + acc1[3]) * f.y, rb);
        bar_arrive(BAR_O, 384);
    }
    KTW(0, 4);
    const uint32_t ra = mapa(sbase + SM_XR + (r * 2 + kh2) * 256 + g * 16 + (t & 1) * 8, mt);
    const uint32_t rb = mapa(bar_xr, mt);
    uint32_t baddr = sbase + SM_HS + (g & 3) * HS_STRIDE + t * 8 + kh2 * 128;
#pragma unroll 1
    for (int br = 0; br < 2; br++) {
        float acc[4][4];
#pragma unroll
        for (int m = 0; m < 4; m++) acc[m][0] = acc[m][1] = acc[m][2] = acc[m][3] = 0.f;
        const int n = br == 0 ? n2 : 10 - n2;
#pragma unroll 1
        for (int j = 0; j < n; j++) {
            uint2 b[4];
            load_b(b, baddr + j * 256, bvalid);
            mbar_wait(bar_full + stage * 8, ph, flag);
            uint32_t a[4][4];
#pragma unroll
            for (int ks = 0; ks < 4; ks++) ldsm_x4_t(a[ks], aoff + stage * STAGE_BYTES + ks * 2048);
#pragma unroll
            for (int ks = 0; ks < 4; ks++) mma16816(acc[ks], a[ks], b[ks].x, b[ks].y);
            if (++stage == NST) { stage = 0; ph ^= 1u; }
        }
        if (t < 2) {
            st_async2(ra + br * 3072, (acc[0][0] + acc[1][0]) + (acc[2][0] + acc[3][0]), (acc[0][1] + acc[1][1]) + (acc[2][1] + acc[3][1]), rb + br * 8);
            st_async2(ra + br * 3072 + 128, (acc[0][2] + acc[1][2]) + (acc[2][2] + acc[3][2]), (acc[0][3] + acc[1][3]) + (acc[2][3] + acc[3][3]), rb + br * 8);
        }
        if (br == 0) {
            KTW(0, 5);
            baddr = sbase + SM_OS + (g & 3) * OS_STRIDE + t * 8 + kh2 * 128;
            bar_sync(BAR_OS, 384);
        }
    }
    if (tid == 0) *reinterpret_cast<volatile unsigned int*>(scr + G_EPOCH + c * 4) = epoch;
}

}
typedef CUresult (*EncodeFn)(CUtensorMap*, CUtensorMapDataType, cuuint32_t, void*, const cuuint64_t*, const cuuint64_t*,
                             const cuuint32_t*, const cuuint32_t*, CUtensorMapInterleave, CUtensorMapSwizzle,
                             CUtensorMapL2promotion, CUtensorMapFloatOOBfill);

void make_2d(EncodeFn enc_fn, CUtensorMap* tm, void* base, uint64_t cols, uint64_t rows, uint32_t box_rows) {
    cuuint64_t gd[2] = {cols, rows};
    cuuint64_t gs[1] = {cols * 2};
    cuuint32_t bd[2] = {64, box_rows};
    cuuint32_t es[2] = {1, 1};
    enc_fn(tm, CU_TENSOR_MAP_DATA_TYPE_BFLOAT16, 2, base, gd, gs, bd, es, CU_TENSOR_MAP_INTERLEAVE_NONE,
           CU_TENSOR_MAP_SWIZZLE_128B, CU_TENSOR_MAP_L2_PROMOTION_L2_128B, CU_TENSOR_MAP_FLOAT_OOB_FILL_NONE);
}
#define PROMO_KV CU_TENSOR_MAP_L2_PROMOTION_L2_256B
#define PROMO_W CU_TENSOR_MAP_L2_PROMOTION_L2_128B
void make_3d(EncodeFn enc_fn, CUtensorMap* tm, void* base, uint64_t cols, uint64_t rows, uint32_t box_rows, uint32_t box_blocks,
             CUtensorMapL2promotion promo = CU_TENSOR_MAP_L2_PROMOTION_L2_128B) {
    cuuint64_t gd[3] = {64, rows, cols / 64};
    cuuint64_t gs[2] = {cols * 2, 128};
    cuuint32_t bd[3] = {64, box_rows, box_blocks};
    cuuint32_t es[3] = {1, 1, 1};
    enc_fn(tm, CU_TENSOR_MAP_DATA_TYPE_BFLOAT16, 3, base, gd, gs, bd, es, CU_TENSOR_MAP_INTERLEAVE_NONE,
           CU_TENSOR_MAP_SWIZZLE_128B, promo, CU_TENSOR_MAP_FLOAT_OOB_FILL_NONE);
}

}

extern "C" void kernel_launch(void* const* d_in, const int* in_sizes, int n_in, void* d_out, int out_size) {
    (void)in_sizes; (void)n_in; (void)out_size;
    static TMaps maps;
    static void* cached[6] = {nullptr, nullptr, nullptr, nullptr, nullptr, nullptr};
    static EncodeFn enc_fn = nullptr;
    static void* scr = nullptr;
    static bool use_c6 = false;
    cudaLaunchConfig_t cfg = {};
    cudaLaunchAttribute at[1];
    cfg.gridDim = dim3(c6::NCTA);
    cfg.blockDim = dim3(c6::NTHREADS);
    cfg.dynamicSmemBytes = c6::SM_ALLOC;
    cfg.stream = cudaStreamPerThread;
    at[0].id = cudaLaunchAttributeClusterDimension;
    at[0].val.clusterDim.x = c6::CS;
    at[0].val.clusterDim.y = 1;
    at[0].val.clusterDim.z = 1;
    cfg.attrs = at;
    cfg.numAttrs = 1;
    if (!enc_fn) {
        void* fn = nullptr;
        cudaDriverEntryPointQueryResult qr;
        cudaGetDriverEntryPoint("cuTensorMapEncodeTiled", &fn, cudaEnableDefault, &qr);
        enc_fn = (EncodeFn)fn;
        cudaFuncSetAttribute(fb::fused_kernel, cudaFuncAttributeMaxDynamicSharedMemorySize, fb::SM_ALLOC);
        cudaFuncSetAttribute(c6::fused_kernel, cudaFuncAttributeMaxDynamicSharedMemorySize, c6::SM_ALLOC);
        int ncl = 0;
        if (cudaOccupancyMaxActiveClusters(&ncl, c6::fused_kernel, &cfg) != cudaSuccess) { ncl = 0; (void)cudaGetLastError(); }
        use_c6 = ncl >= c6::NCL;
        if (use_c6) cudaGetSymbolAddress(&scr, c6::g_scratch);
        else cudaGetSymbolAddress(&scr, fb::g_scratch);
    }
    void* cur[6] = {d_in[3], d_in[6], d_in[1], d_in[2], d_in[8], d_in[4]};
    bool same = true;
    for (int i = 0; i < 6; i++) same = same && (cur[i] == cached[i]);
    if (!same) {
        make_2d(enc_fn, &maps.wq, d_in[3], 4096, 1024, 128);
        make_2d(enc_fn, &maps.w1, d_in[6], F_DIM, 1024, 128);
        make_3d(enc_fn, &maps.k, d_in[1], 128, 16 * SK, 64, 2, PROMO_KV);
        make_3d(enc_fn, &maps.v, d_in[2], 128, 16 * SK, 64, 2, PROMO_KV);
        make_3d(enc_fn, &maps.w2, d_in[8], 1024, F_DIM, 16, 4);
        make_3d(enc_fn, &maps.wo, d_in[4], 1024, 4096, 16, 4);
        make_3d(enc_fn, &maps.w2n, d_in[8], 1024, F_DIM, 128, 1, PROMO_W);
        make_3d(enc_fn, &maps.wq3, d_in[3], 4096, 1024, 128, 1, PROMO_W);
        make_3d(enc_fn, &maps.won, d_in[4], 1024, 4096, 128, 1, PROMO_W);
        make_3d(enc_fn, &maps.w1n, d_in[6], F_DIM, 1024, 128, 1, PROMO_W);
        for (int i = 0; i < 6; i++) cached[i] = cur[i];
    }
    if (use_c6) {
        cudaLaunchKernelEx(&cfg, c6::fused_kernel, (const __nv_bfloat16*)d_in[3], (const __nv_bfloat16*)d_in[0],
                           (unsigned int*)scr, (__nv_bfloat16*)d_out, (const __nv_bfloat16*)d_in[10],
                           (const __nv_bfloat16*)d_in[7], maps, (const __nv_bfloat16*)d_in[9]);
    } else {
        fb::fused_kernel<<<fb::NCTA, fb::NTHREADS, fb::SM_ALLOC, cudaStreamPerThread>>>(
            (const __nv_bfloat16*)d_in[3], (const __nv_bfloat16*)d_in[0], (unsigned int*)scr, (__nv_bfloat16*)d_out,
            (const __nv_bfloat16*)d_in[10], (const __nv_bfloat16*)d_in[7], maps, (const __nv_bfloat16*)d_in[9]);
    }
}
```

```cpp
#include <cuda_runtime.h>
#include <cuda.h>
#include <cuda_bf16.h>
#include <stdint.h>

namespace {

constexpr int NSTAGE = 12;
constexpr int STAGE_BYTES = 16384;

constexpr int D_MODEL = 1024;
constexpr int F_DIM = 3584;
constexpr int SK = 8192;

constexpr int XS_STRIDE = 1032 * 2;
constexpr int FR_STRIDE = 288;

#define PACE_T 652
#define PACE_LEAD 2
#define PACE_OFF PACE_T
#define PW_J 6
#define PACE_CAP 4
#define FP_GAP 160
#define OG_DELAY 400

constexpr int BAR_INIT = 0;
constexpr int BAR_CONS = 1;
constexpr int BAR_PAIR = 2;
constexpr int BAR_X = 6;
constexpr int BAR_ML = 7;
constexpr int BAR_O = 8;
constexpr int BAR_OS = 9;
constexpr int BAR_W1 = 10;
constexpr int BAR_HS = 11;
constexpr int BAR_A = 12;
constexpr int BAR_B = 13;
constexpr int BAR_F = 14;

struct TMaps {
    CUtensorMap wq, w1, k, v, w2, wo, w2n, w1n, wq3, won;
};

__device__ __forceinline__ uint32_t smem_u32(const void* p) { return (uint32_t)__cvta_generic_to_shared(p); }
__device__ __forceinline__ uint32_t gtime32() { uint32_t t; asm volatile("mov.u32 %0, %globaltimer_lo;" : "=r"(t)); return t; }

__device__ __forceinline__ void mbar_init(uint32_t bar, uint32_t cnt) {
    asm volatile("mbarrier.init.shared::cta.b64 [%0], %1;" ::"r"(bar), "r"(cnt) : "memory");
}
__device__ __forceinline__ void mbar_expect_tx(uint32_t bar, uint32_t bytes) {
    asm volatile("mbarrier.arrive.expect_tx.shared::cta.b64 _, [%0], %1;" ::"r"(bar), "r"(bytes) : "memory");
}
__device__ __forceinline__ void mbar_arrive_cnt(uint32_t bar, uint32_t cnt) {
    asm volatile("mbarrier.arrive.shared::cta.b64 _, [%0], %1;" ::"r"(bar), "r"(cnt) : "memory");
}
__device__ __forceinline__ bool mbar_try(uint32_t bar, uint32_t parity) {
    uint32_t ok;
    asm volatile(
        "{\n.reg .pred p;\n"
        "mbarrier.try_wait.parity.shared::cta.b64 p, [%1], %2;\n"
        "selp.u32 %0, 1, 0, p;\n}\n"
        : "=r"(ok)
        : "r"(bar), "r"(parity)
        : "memory");
    return ok != 0;
}
__device__ __noinline__ void mbar_wait_slow(uint32_t bar, uint32_t parity, volatile uint32_t* flag) {
    long long t0 = clock64();
    for (uint32_t it = 0; it < 0x40000000u; it++) {
        if (mbar_try(bar, parity)) return;
        if ((it & 63u) == 63u) {
            if (*flag) return;
            if (clock64() - t0 > 2000000000LL) { *flag = 1u; return; }
        }
    }
}
__device__ __forceinline__ void mbar_wait(uint32_t bar, uint32_t parity, volatile uint32_t* flag) {
    if (mbar_try(bar, parity)) return;
    if (mbar_try(bar, parity)) return;
    mbar_wait_slow(bar, parity, flag);
}

__device__ __forceinline__ void mbar_wait_cluster(uint32_t bar, volatile uint32_t* flag) {
    const long long t0 = clock64();
    for (uint32_t it = 0; it < 0x40000000u; it++) {
        uint32_t ok;
        asm volatile(
            "{\n.reg .pred p;\n"
            "mbarrier.try_wait.parity.acquire.cluster.shared::cta.b64 p, [%1], 0;\n"
            "selp.u32 %0, 1, 0, p;\n}\n"
            : "=r"(ok)
            : "r"(bar)
            : "memory");
        if (ok) return;
        if ((it & 63u) == 63u && (*flag || clock64() - t0 > 4000000000LL)) return;
    }
}

__device__ __forceinline__ void tma_2d(uint32_t dst, const CUtensorMap* tm, int c0, int c1, uint32_t bar) {
    asm volatile(
        "cp.async.bulk.tensor.2d.shared::cluster.global.mbarrier::complete_tx::bytes.L2::cache_hint [%0], [%1, {%3, %4}], [%2], %5;"
        ::"r"(dst), "l"(tm), "r"(bar), "r"(c0), "r"(c1), "l"(0x12F0000000000000ull)
        : "memory");
}
__device__ __forceinline__ void tma_3d(uint32_t dst, const CUtensorMap* tm, int c0, int c1, int c2, uint32_t bar) {
    asm volatile(
        "cp.async.bulk.tensor.3d.shared::cluster.global.mbarrier::complete_tx::bytes.L2::cache_hint [%0], [%1, {%3, %4, %5}], [%2], %6;"
        ::"r"(dst), "l"(tm), "r"(bar), "r"(c0), "r"(c1), "r"(c2), "l"(0x12F0000000000000ull)
        : "memory");
}
__device__ __forceinline__ void bulk_load(uint32_t dst, const void* src, uint32_t bytes, uint32_t bar) {
    asm volatile("cp.async.bulk.shared::cluster.global.mbarrier::complete_tx::bytes [%0], [%1], %2, [%3];"
                 ::"r"(dst), "l"(src), "r"(bytes), "r"(bar)
                 : "memory");
}
__device__ __forceinline__ void prefetch_tmap(const CUtensorMap* tm) {
    asm volatile("prefetch.tensormap [%0];" ::"l"(tm) : "memory");
}
__device__ __forceinline__ void bar_sync(int id, int cnt) { asm volatile("bar.sync %0, %1;" ::"r"(id), "r"(cnt) : "memory"); }
__device__ __forceinline__ void bar_arrive(int id, int cnt) { asm volatile("bar.arrive %0, %1;" ::"r"(id), "r"(cnt) : "memory"); }

__device__ __forceinline__ void ldsm_x4(uint32_t (&r)[4], uint32_t addr) {
    asm volatile("ldmatrix.sync.aligned.m8n8.x4.shared.b16 {%0,%1,%2,%3}, [%4];"
                 : "=r"(r[0]), "=r"(r[1]), "=r"(r[2]), "=r"(r[3])
                 : "r"(addr)
                 : "memory");
}
__device__ __forceinline__ void ldsm_x4_t(uint32_t (&r)[4], uint32_t addr) {
    asm volatile("ldmatrix.sync.aligned.m8n8.x4.trans.shared.b16 {%0,%1,%2,%3}, [%4];"
                 : "=r"(r[0]), "=r"(r[1]), "=r"(r[2]), "=r"(r[3])
                 : "r"(addr)
                 : "memory");
}
__device__ __forceinline__ void mma16816(float (&c)[4], const uint32_t (&a)[4], uint32_t b0, uint32_t b1) {
    asm volatile(
        "mma.sync.aligned.m16n8k16.row.col.f32.bf16.bf16.f32 {%0,%1,%2,%3}, {%4,%5,%6,%7}, {%8,%9}, {%0,%1,%2,%3};"
        : "+f"(c[0]), "+f"(c[1]), "+f"(c[2]), "+f"(c[3])
        : "r"(a[0]), "r"(a[1]), "r"(a[2]), "r"(a[3]), "r"(b0), "r"(b1));
}
__device__ __forceinline__ uint32_t lds32(uint32_t addr) {
    uint32_t v;
    asm volatile("ld.shared.b32 %0, [%1];" : "=r"(v) : "r"(addr) : "memory");
    return v;
}
__device__ __forceinline__ uint2 lds64(uint32_t addr) {
    uint2 v;
    asm volatile("ld.shared.v2.b32 {%0, %1}, [%2];" : "=r"(v.x), "=r"(v.y) : "r"(addr) : "memory");
    return v;
}
__device__ __forceinline__ void sts32(uint32_t addr, uint32_t v) {
    asm volatile("st.shared.b32 [%0], %1;" ::"r"(addr), "r"(v) : "memory");
}
__device__ __forceinline__ void sts64(uint32_t addr, uint32_t a, uint32_t b) {
    asm volatile("st.shared.v2.b32 [%0], {%1, %2};" ::"r"(addr), "r"(a), "r"(b) : "memory");
}

__device__ __forceinline__ float bf16r(float x) { return __bfloat162float(__float2bfloat16_rn(x)); }
__device__ __forceinline__ uint32_t pack_bf16(float lo, float hi) {
    __nv_bfloat162 v = __floats2bfloat162_rn(lo, hi);
    return *reinterpret_cast<uint32_t*>(&v);
}
__device__ __forceinline__ float bf_lo(uint32_t u) { return __uint_as_float(u << 16); }
__device__ __forceinline__ float bf_hi(uint32_t u) { return __uint_as_float(u & 0xffff0000u); }

__device__ __forceinline__ uint32_t enc(float v, uint32_t tag) { return (__float_as_uint(v) & ~3u) | tag; }
__device__ __forceinline__ float dec(uint32_t u) { return __uint_as_float(u & ~3u); }
__device__ __forceinline__ void st2(unsigned int* p, uint32_t a, uint32_t b) {
    asm volatile("st.relaxed.gpu.global.v2.b32 [%0], {%1, %2};" ::"l"(p), "r"(a), "r"(b) : "memory");
}
__device__ __forceinline__ void st4(unsigned int* p, uint32_t a, uint32_t b, uint32_t c, uint32_t d) {
    asm volatile("st.relaxed.gpu.global.v4.b32 [%0], {%1, %2, %3, %4};" ::"l"(p), "r"(a), "r"(b), "r"(c), "r"(d) : "memory");
}
__device__ __forceinline__ uint32_t ld1(const unsigned int* p) {
    uint32_t v;
    asm volatile("ld.relaxed.gpu.global.b32 %0, [%1];" : "=r"(v) : "l"(p) : "memory");
    return v;
}
__device__ __forceinline__ uint2 ld2(const unsigned int* p) {
    uint2 v;
    asm volatile("ld.relaxed.gpu.global.v2.b32 {%0, %1}, [%2];" : "=r"(v.x), "=r"(v.y) : "l"(p) : "memory");
    return v;
}
__device__ __forceinline__ uint4 ld4(const unsigned int* p) {
    uint4 v;
    asm volatile("ld.relaxed.gpu.global.v4.b32 {%0, %1, %2, %3}, [%4];" : "=r"(v.x), "=r"(v.y), "=r"(v.z), "=r"(v.w) : "l"(p) : "memory");
    return v;
}
__device__ __forceinline__ uint32_t bad4(const uint4& v, uint32_t tag) { return (v.x ^ tag) | (v.y ^ tag) | (v.z ^ tag) | (v.w ^ tag); }
__device__ __forceinline__ bool warp_ok(uint32_t bad) { return __all_sync(0xffffffffu, (bad & 3u) == 0u); }
__device__ __forceinline__ void spin_cycles(int n) {
    const uint32_t t0 = (uint32_t)clock64();
    for (int it = 0; it < 1000 && (int)((uint32_t)clock64() - t0) < n; it++) {}
}
constexpr uint32_t POLL_LIMIT = 1u << 21;

__device__ __forceinline__ void gemv_tile4(float (&acc0)[4], float (&acc1)[4], uint32_t a_addr, uint32_t b_addr, bool bvalid) {
    uint32_t a[4][4];
    uint32_t b[4][2];
#pragma unroll
    for (int ks = 0; ks < 4; ks++) ldsm_x4_t(a[ks], a_addr + ks * 2048);
#pragma unroll
    for (int ks = 0; ks < 4; ks++) {
        b[ks][0] = bvalid ? lds32(b_addr + ks * 32) : 0u;
        b[ks][1] = bvalid ? lds32(b_addr + ks * 32 + 16) : 0u;
    }
#pragma unroll
    for (int ks = 0; ks < 4; ks++) {
        if (ks & 1) mma16816(acc1, a[ks], b[ks][0], b[ks][1]);
        else mma16816(acc0, a[ks], b[ks][0], b[ks][1]);
    }
}

template <int N>
__device__ __forceinline__ float final_sum(const unsigned int* buf, int lane, uint32_t tag, bool backoff) {
    const unsigned int* p = buf + (lane >> 3) * (N * 32) + (lane & 7) * 4;
    uint4 d[N];
    for (uint32_t it = 0; it < POLL_LIMIT; it++) {
        uint32_t bad = 0;
#pragma unroll
        for (int i = 0; i < N; i++) { d[i] = ld4(p + i * 32); bad |= bad4(d[i], tag); }
        if (warp_ok(bad)) break;
        if (backoff) __nanosleep(100);
    }
    float s0 = 0.f, s1 = 0.f, s2 = 0.f, s3 = 0.f;
#pragma unroll
    for (int i = 0; i < N; i++) { s0 += dec(d[i].x); s1 += dec(d[i].y); s2 += dec(d[i].z); s3 += dec(d[i].w); }
    const bool hi = lane & 16;
    float u0 = hi ? s0 : s2, u1 = hi ? s1 : s3;
    float k0 = hi ? s2 : s0, k1 = hi ? s3 : s1;
    k0 += __shfl_xor_sync(0xffffffffu, u0, 16);
    k1 += __shfl_xor_sync(0xffffffffu, u1, 16);
    const bool od = lane & 8;
    const float w = od ? k0 : k1;
    float r = od ? k1 : k0;
    r += __shfl_xor_sync(0xffffffffu, w, 8);
    return r;
}

namespace fb {

constexpr int NCTA = 128;
constexpr int NTHREADS = 416;

constexpr int SM_P = NSTAGE * STAGE_BYTES;
constexpr int SM_XS = SM_P;
constexpr int SM_YS = SM_P + 16384;
constexpr int SM_QS = SM_YS + 4160;
constexpr int SM_OS = SM_QS + 2304;
constexpr int SM_HS = SM_OS + 1152;
constexpr int SM_RED = SM_HS + 960;
constexpr int SM_MX = SM_RED + 2048;
constexpr int SM_LS = SM_MX + 256;
constexpr int SM_F = SM_LS + 256;
constexpr int SM_BAR = SM_F + 32;
constexpr int SM_FLAG = SM_BAR + 2 * NSTAGE * 8;
constexpr int SM_TOTAL = SM_FLAG + 8;
constexpr int SM_ALLOC = SM_TOTAL + 1024;

constexpr int YS_STRIDE = 520 * 2;
constexpr int HS_STRIDE = 240;

constexpr int G_EPOCH = 0;
constexpr int G_Q = G_EPOCH + NCTA * 4;
constexpr int G_H = G_Q + 2 * 4 * 4096;
constexpr int G_ML = G_H + 2 * F_DIM * 4;
constexpr int G_O = G_ML + NCTA * 16;
constexpr int G_A = G_O + NCTA * 1024;
constexpr int G_B = G_A + NCTA * 1024;
constexpr int G_TOTAL = G_B + NCTA * 1024;
__device__ __align__(1024) unsigned int g_scratch[G_TOTAL];

__global__ void __launch_bounds__(NTHREADS, 1)
fused_kernel(const __nv_bfloat16* __restrict__ wq, const __nv_bfloat16* __restrict__ x, unsigned int* __restrict__ scr,
             __nv_bfloat16* __restrict__ out, const __nv_bfloat16* __restrict__ gate_w, const __nv_bfloat16* __restrict__ b1,
             const __grid_constant__ TMaps maps, const __nv_bfloat16* __restrict__ b2) {
    extern __shared__ unsigned char smem_raw[];
    const uint32_t sbase = (smem_u32(smem_raw) + 1023u) & ~1023u;
    unsigned char* sptr = smem_raw + (sbase - smem_u32(smem_raw));
    volatile uint32_t* flag = reinterpret_cast<volatile uint32_t*>(sptr + SM_FLAG);

    const int c = blockIdx.x;
    const int tid = threadIdx.x;
    const int warp = tid >> 5;
    const int lane = tid & 31;
    const bool has_w1 = c < 112;
    const int kb = c >> 2, nb = c & 3;
    const uint32_t bar_full = sbase + SM_BAR;
    const uint32_t bar_empty = sbase + SM_BAR + NSTAGE * 8;

    if (warp == 8) {
        const int n_w1 = has_w1 ? 4 : 0;
        const int n_tiles = 44 + n_w1;
        const int kv_row0 = (c >> 3) * SK + (c & 7) * 1024;
        uint32_t due = 0;
        if (lane == 0) {
#pragma unroll
            for (int j = 0; j < PACE_LEAD; j++) mbar_init(bar_full + j * 8, 1);
            asm volatile("fence.mbarrier_init.release.cluster;" ::: "memory");
            asm volatile("fence.proxy.async.shared::cta;" ::: "memory");
#pragma unroll
            for (int j = 0; j < PACE_LEAD; j++) {
                mbar_expect_tx(bar_full + j * 8, STAGE_BYTES);
                tma_2d(sbase + j * STAGE_BYTES, &maps.wq, (c >> 1) * 64, (c & 1) * 512 + j * 128, bar_full + j * 8);
            }
            due = gtime32() + PACE_OFF + (c >> 1) * PACE_T / 64;
#pragma unroll
            for (int i = PACE_LEAD; i < NSTAGE; i++) mbar_init(bar_full + i * 8, 1);
#pragma unroll
            for (int i = 0; i < NSTAGE; i++) mbar_init(bar_empty + i * 8, 8);
            *flag = 0u;
            asm volatile("fence.mbarrier_init.release.cluster;" ::: "memory");
            asm volatile("fence.proxy.async.shared::cta;" ::: "memory");
            prefetch_tmap(&maps.w1);
            prefetch_tmap(&maps.k);
            prefetch_tmap(&maps.v);
            prefetch_tmap(&maps.w2);
            prefetch_tmap(&maps.wo);
        }
        __syncwarp();
        bar_arrive(BAR_INIT, NTHREADS);
        if (lane == 0) {
            int landed = 0;
            for (int i = PACE_LEAD; i < n_tiles; i++) {
                while (landed + PACE_CAP <= i) {
                    mbar_wait(bar_full + (landed % NSTAGE) * 8, (uint32_t)(landed / NSTAGE) & 1u, flag);
                    landed++;
                }
                const int stage = i % NSTAGE;
                if (i >= NSTAGE) mbar_wait(bar_empty + stage * 8, (uint32_t)(i / NSTAGE - 1) & 1u, flag);
                for (int it = 0; it < 100000 && (int)(gtime32() - due) < 0; it++) {}
                const uint32_t dst = sbase + stage * STAGE_BYTES;
                const uint32_t fb = bar_full + stage * 8;
                int j = i - 4;
                if (j < 0) {
                    mbar_expect_tx(fb, STAGE_BYTES);
                    tma_2d(dst, &maps.wq, (c >> 1) * 64, (c & 1) * 512 + i * 128, fb);
                    due += (j == -1 && !has_w1) ? PACE_T * 9 / 2 : PACE_T;
                } else if (j < n_w1) {
                    mbar_expect_tx(fb, STAGE_BYTES);
                    tma_2d(dst, &maps.w1, (c >> 1) * 64, (c & 1) * 512 + j * 128, fb);
                    due += PACE_T * 7 / 8;
                } else if (j < 32 + n_w1) {
                    j -= n_w1;
                    mbar_expect_tx(fb, STAGE_BYTES);
                    tma_3d(dst, j < 16 ? &maps.k : &maps.v, 0, kv_row0 + (j & 15) * 64, 0, fb);
                    due += PACE_T;
                } else {
                    j -= 32 + n_w1;
                    const CUtensorMap* tm = j < 4 ? &maps.w2 : &maps.wo;
                    const int row = j < 4 ? kb * 112 + j * 32 : kb * 128 + (j - 4) * 32;
                    mbar_expect_tx(fb, j != 3 ? STAGE_BYTES : STAGE_BYTES / 2);
                    tma_3d(dst, tm, 0, row, nb * 4, fb);
                    if (j != 3) tma_3d(dst + 8192, tm, 0, row + 16, nb * 4, fb);
                    due += j != 3 ? PACE_T : PACE_T / 2;
                }
            }
        }
        return;
    }

    const int g = lane >> 2;
    const int t = lane & 3;
    const int khalf = c & 1;
    const int pair = c >> 3;
    const int mt = warp & 3;
    const int kh2 = warp >> 2;
    const uint32_t epoch = ld1(scr + G_EPOCH + c * 4) + 1u;
    unsigned int* const q_dst = scr + G_Q + (khalf * 4 + 2 * t) * 4096 + (c >> 1) * 64 + mt * 16 + 2 * g;
    unsigned int* const h_dst = scr + G_H + (khalf * F_DIM + (c >> 1) * 64 + mt * 16 + g) * 4 + 2 * t;
    if (warp < 8) {
        asm volatile("prefetch.global.L2 [%0];" ::"l"(wq + (size_t)(khalf * 512 + tid) * 4096 + (c >> 1) * 64));
        const uint4 x0 = __ldg(reinterpret_cast<const uint4*>(x) + tid);
        const uint4 x1 = __ldg(reinterpret_cast<const uint4*>(x) + 256 + tid);
        if (warp < 4 && t < 2) {
            st2(q_dst, 0u, 0u);
            st2(q_dst + 4096, 0u, 0u);
            if (has_w1) {
                st2(h_dst, 0u, 0u);
                st2(h_dst + 32, 0u, 0u);
            }
        }
        *reinterpret_cast<uint4*>(sptr + SM_XS + (tid >> 7) * XS_STRIDE + (tid & 127) * 16) = x0;
        *reinterpret_cast<uint4*>(sptr + SM_XS + (2 + (tid >> 7)) * XS_STRIDE + (tid & 127) * 16) = x1;
    }
    const uint32_t tag = 1u + epoch % 3u;

    if (warp >= 9) {
        float gate = 0.f, b2v = 0.f;
        if (warp == 9) {
            uint4 gw[4];
#pragma unroll
            for (int i = 0; i < 4; i++) gw[i] = __ldg(reinterpret_cast<const uint4*>(gate_w) + i * 32 + lane);
            b2v = __bfloat162float(b2[c * 8 + (lane & 7)]);
            bar_sync(BAR_INIT, NTHREADS);
            float zz = 0.f;
#pragma unroll 1
            for (int b = 0; b < 4; b++) {
                float zs = 0.f;
#pragma unroll
                for (int i = 0; i < 4; i++) {
                    const uint4 xv = *reinterpret_cast<const uint4*>(sptr + SM_XS + b * XS_STRIDE + (i * 32 + lane) * 16);
                    const uint32_t xa[4] = {xv.x, xv.y, xv.z, xv.w};
                    const uint32_t wa[4] = {gw[i].x, gw[i].y, gw[i].z, gw[i].w};
#pragma unroll
                    for (int e = 0; e < 4; e++) {
                        zs += bf16r(bf_lo(xa[e]) * bf_lo(wa[e]));
                        zs += bf16r(bf_hi(xa[e]) * bf_hi(wa[e]));
                    }
                }
#pragma unroll
                for (int o = 16; o > 0; o >>= 1) zs += __shfl_xor_sync(0xffffffffu, zs, o);
                if ((lane >> 3) == b) zz = zs;
            }
            bar_arrive(BAR_X, 288);
            zz = bf16r(zz);
            gate = bf16r(1.0f / (1.0f + __expf(-zz)));
            if (lane == 0) *reinterpret_cast<volatile unsigned int*>(scr + G_EPOCH + c * 4) = epoch;
        } else if (warp == 11) {
            const bool has4 = lane < 16;
            float bias[4];
#pragma unroll
            for (int i = 0; i < 4; i++) bias[i] = (i < 3 || has4) ? __bfloat162float(b1[kb * 112 + i * 32 + lane]) : 0.f;
            bar_sync(BAR_INIT, NTHREADS);
            bar_sync(BAR_W1, 288);
            const unsigned int* p = scr + G_H + (kb * 112 + lane) * 4;
            uint4 d[4][2];
            for (uint32_t it = 0; it < POLL_LIMIT; it++) {
                __nanosleep(1000);
                uint32_t bad = 0;
#pragma unroll
                for (int i = 0; i < 4; i++) {
                    if (i < 3 || has4) {
                        d[i][0] = ld4(p + i * 128);
                        d[i][1] = ld4(p + i * 128 + F_DIM * 4);
                        bad |= bad4(d[i][0], tag) | bad4(d[i][1], tag);
                    }
                }
                if (warp_ok(bad)) break;
            }
#pragma unroll
            for (int i = 0; i < 4; i++) {
                if (i < 3 || has4) {
                    const int cl = i * 32 + lane;
                    const uint32_t u0[4] = {d[i][0].x, d[i][0].y, d[i][0].z, d[i][0].w};
                    const uint32_t u1[4] = {d[i][1].x, d[i][1].y, d[i][1].z, d[i][1].w};
#pragma unroll
                    for (int b = 0; b < 4; b++) {
                        float v = bf16r(dec(u0[b]) + dec(u1[b]));
                        v = bf16r(v + bias[i]);
                        const float inner = 0.7978845608028654f * (v + 0.044715f * v * v * v);
                        const float hv = 0.5f * v * (1.0f + tanhf(inner));
                        *reinterpret_cast<__nv_bfloat16*>(sptr + SM_HS + b * HS_STRIDE + cl * 2) = __float2bfloat16_rn(hv);
                    }
                }
            }
            bar_arrive(BAR_HS, 288);
        } else if (warp == 12) {
            bar_sync(BAR_INIT, NTHREADS);
            bar_sync(BAR_ML, 64);
            const unsigned int* p = scr + G_ML + pair * 128 + lane * 4;
            uint4 d;
            for (uint32_t it = 0; it < POLL_LIMIT; it++) {
                __nanosleep(1000);
                d = ld4(p);
                if (warp_ok(bad4(d, tag))) break;
            }
            const float m0 = dec(d.x), m1 = dec(d.z);
            float M0 = m0, M1 = m1;
#pragma unroll
            for (int o = 4; o < 32; o <<= 1) {
                M0 = fmaxf(M0, __shfl_xor_sync(0xffffffffu, M0, o));
                M1 = fmaxf(M1, __shfl_xor_sync(0xffffffffu, M1, o));
            }
            const float w0 = exp2f((m0 - M0) * 1.4426950408889634f), w1 = exp2f((m1 - M1) * 1.4426950408889634f);
            float L0 = w0 * dec(d.y), L1 = w1 * dec(d.w);
#pragma unroll
            for (int o = 4; o < 32; o <<= 1) {
                L0 += __shfl_xor_sync(0xffffffffu, L0, o);
                L1 += __shfl_xor_sync(0xffffffffu, L1, o);
            }
            if (g == (c & 7)) *reinterpret_cast<float2*>(sptr + SM_F + t * 8) = make_float2(w0 / L0, w1 / L1);
            bar_arrive(BAR_F, 288);
        } else {
            bar_sync(BAR_INIT, NTHREADS);
        }
        {
            const int hb = warp - 9;
            const unsigned int* po = scr + G_O + ((hb * 4 + (kb >> 3)) * 8 + (kb & 7)) * 1024 + lane * 4;
            uint4 d[8];
            uint32_t pend = 0xffu;
            bar_sync(BAR_O, 384);
            __nanosleep(OG_DELAY);
            for (uint32_t it = 0; it < POLL_LIMIT; it++) {
#pragma unroll
                for (int s = 0; s < 8; s++)
                    if (pend & (1u << s)) d[s] = ld4(po + s * 128);
#pragma unroll
                for (int s = 0; s < 8; s++)
                    if ((pend & (1u << s)) && warp_ok(bad4(d[s], tag))) pend &= ~(1u << s);
                if (pend == 0u) break;
                __nanosleep(100);
            }
            float o0 = 0.f, o1 = 0.f, o2 = 0.f, o3 = 0.f;
#pragma unroll
            for (int s = 0; s < 8; s++) {
                o0 += dec(d[s].x);
                o1 += dec(d[s].y);
                o2 += dec(d[s].z);
                o3 += dec(d[s].w);
            }
            sts64(sbase + SM_OS + hb * FR_STRIDE + lane * 8, pack_bf16(o0, o2), pack_bf16(o1, o3));
            bar_arrive(BAR_OS, 384);
        }
        if (warp != 9) return;
        bar_sync(BAR_B, 288);
        const float bv = bf16r(bf16r(final_sum<8>(scr + G_B + c * 1024, lane, tag, true)) + b2v);
        const float bterm = bf16r(bf16r(1.0f - gate) * bv);
        bar_sync(BAR_A, 288);
        const float aterm = bf16r(gate * bf16r(final_sum<8>(scr + G_A + c * 1024, lane, tag, false)));
        out[(lane >> 3) * D_MODEL + c * 8 + (lane & 7)] = __float2bfloat16_rn(aterm + bterm);
        return;
    }

    bar_sync(BAR_INIT, NTHREADS);

    int stage = 0;
    uint32_t ph = 0;
    const uint32_t l8 = lane & 7;
    const uint32_t rowT = (l8 + 8 * (lane >> 4)) * 128;
    const uint32_t offT = rowT + ((((uint32_t)(2 * mt + ((lane >> 3) & 1))) ^ l8) << 4);
    const bool bvalid = g < 4;
    const int dst_off = ((nb * 32 + warp * 4) * 32 + kb) * 32 + g * 4 + 2 * t;

    {
        float acc0[4] = {0.f, 0.f, 0.f, 0.f}, acc1[4] = {0.f, 0.f, 0.f, 0.f};
        const uint32_t baddr = sbase + SM_XS + (g & 3) * XS_STRIDE + (khalf * 512 + kh2 * 64 + 2 * t) * 2;
#pragma unroll 1
        for (int j = 0; j < 4; j++) {
            mbar_wait(bar_full + stage * 8, ph, flag);
            gemv_tile4(acc0, acc1, sbase + stage * STAGE_BYTES + kh2 * 8192 + offT, baddr + j * 256, bvalid);
            __syncwarp();
            if (lane == 0) mbar_arrive_cnt(bar_empty + stage * 8, 1);
            ++stage;
        }
        float4* red = reinterpret_cast<float4*>(sptr + SM_RED) + mt * 16 + (g * 2 + (t & 1));
        if (kh2 == 1 && t < 2) *red = make_float4(acc0[0] + acc1[0], acc0[1] + acc1[1], acc0[2] + acc1[2], acc0[3] + acc1[3]);
        bar_sync(BAR_PAIR + mt, 64);
        if (kh2 == 0 && t < 2) {
            const float4 o = *red;
            st2(q_dst, enc(acc0[0] + acc1[0] + o.x, tag), enc(acc0[2] + acc1[2] + o.z, tag));
            st2(q_dst + 4096, enc(acc0[1] + acc1[1] + o.y, tag), enc(acc0[3] + acc1[3] + o.w, tag));
        }
    }
    if (has_w1) {
        {
            uint4 xv[4];
#pragma unroll
            for (int i = 0; i < 4; i++) xv[i] = *reinterpret_cast<const uint4*>(sptr + SM_XS + mt * XS_STRIDE + (i * 32 + lane) * 16);
            const uint4 xs = *reinterpret_cast<const uint4*>(sptr + SM_XS + mt * XS_STRIDE + (khalf * 64 + kh2 * 32 + lane) * 16);
            float s0 = 0.f, s1 = 0.f;
#pragma unroll
            for (int i = 0; i < 4; i++) {
                const uint32_t xa[4] = {xv[i].x, xv[i].y, xv[i].z, xv[i].w};
#pragma unroll
                for (int e = 0; e < 4; e++) { s0 += bf_lo(xa[e]); s1 += bf_hi(xa[e]); }
            }
            float s = s0 + s1;
#pragma unroll
            for (int o = 16; o > 0; o >>= 1) s += __shfl_xor_sync(0xffffffffu, s, o);
            const float mean = s * (1.0f / 1024.0f);
            float q0 = 0.f, q1 = 0.f;
#pragma unroll
            for (int i = 0; i < 4; i++) {
                const uint32_t xa[4] = {xv[i].x, xv[i].y, xv[i].z, xv[i].w};
#pragma unroll
                for (int e = 0; e < 4; e++) {
                    const float d0 = bf_lo(xa[e]) - mean, d1 = bf_hi(xa[e]) - mean;
                    q0 = fmaf(d0, d0, q0);
                    q1 = fmaf(d1, d1, q1);
                }
            }
            float q = q0 + q1;
#pragma unroll
            for (int o = 16; o > 0; o >>= 1) q += __shfl_xor_sync(0xffffffffu, q, o);
            const float mb = bf16r(mean);
            const float vb = bf16r(q * (1.0f / 1024.0f));
            const float den = bf16r(sqrtf(bf16r(vb + 1e-5f)));
            const uint32_t xa[4] = {xs.x, xs.y, xs.z, xs.w};
            uint32_t ya[4];
#pragma unroll
            for (int e = 0; e < 4; e++) ya[e] = pack_bf16(bf16r(bf_lo(xa[e]) - mb) / den, bf16r(bf_hi(xa[e]) - mb) / den);
            *reinterpret_cast<uint4*>(sptr + SM_YS + mt * YS_STRIDE + (kh2 * 32 + lane) * 16) = make_uint4(ya[0], ya[1], ya[2], ya[3]);
            bar_sync(BAR_CONS, 256);
        }
        float acc0[4] = {0.f, 0.f, 0.f, 0.f}, acc1[4] = {0.f, 0.f, 0.f, 0.f};
        const uint32_t baddr = sbase + SM_YS + (g & 3) * YS_STRIDE + (kh2 * 64 + 2 * t) * 2;
#pragma unroll 1
        for (int j = 0; j < 4; j++) {
            mbar_wait(bar_full + stage * 8, ph, flag);
            gemv_tile4(acc0, acc1, sbase + stage * STAGE_BYTES + kh2 * 8192 + offT, baddr + j * 256, bvalid);
            __syncwarp();
            if (lane == 0) mbar_arrive_cnt(bar_empty + stage * 8, 1);
            ++stage;
        }
        float4* red = reinterpret_cast<float4*>(sptr + SM_RED + 1024) + mt * 16 + (g * 2 + (t & 1));
        if (kh2 == 1 && t < 2) *red = make_float4(acc0[0] + acc1[0], acc0[1] + acc1[1], acc0[2] + acc1[2], acc0[3] + acc1[3]);
        bar_sync(BAR_PAIR + mt, 64);
        if (kh2 == 0 && t < 2) {
            const float4 o = *red;
            st2(h_dst, enc(acc0[0] + acc1[0] + o.x, tag), enc(acc0[1] + acc1[1] + o.y, tag));
            st2(h_dst + 32, enc(acc0[2] + acc1[2] + o.z, tag), enc(acc0[3] + acc1[3] + o.w, tag));
        }
    } else {
        mbar_wait(bar_full + stage * 8, ph, flag);
    }
    bar_arrive(BAR_W1, 288);
    uint32_t qf[8][2];
    {
        const unsigned int* p = scr + G_Q + (pair >> 2) * 4096 + (pair & 3) * 1024 + tid * 4;
        uint4 d0, d1;
        for (uint32_t it = 0; it < POLL_LIMIT; it++) {
            d0 = ld4(p);
            d1 = ld4(p + 4 * 4096);
            if (warp_ok(bad4(d0, tag) | bad4(d1, tag))) break;
            __nanosleep(200);
        }
        sts64(sbase + SM_QS + warp * FR_STRIDE + lane * 8,
              pack_bf16(dec(d0.x) + dec(d1.x), dec(d0.z) + dec(d1.z)), pack_bf16(dec(d0.y) + dec(d1.y), dec(d0.w) + dec(d1.w)));
        bar_sync(BAR_CONS, 256);
#pragma unroll
        for (int ks = 0; ks < 8; ks++) {
            const uint2 v = lds64(sbase + SM_QS + g * FR_STRIDE + (ks * 4 + t) * 8);
            qf[ks][0] = v.x;
            qf[ks][1] = v.y;
        }
    }
    float sc[8][4];
    {
        int st = stage + kh2;
        uint32_t php = ph;
        const uint32_t krow = mt * 16 + l8 + 8 * ((lane >> 3) & 1);
        const uint32_t khi = lane >> 4;
#pragma unroll
        for (int i = 0; i < 8; i++) {
            mbar_wait(bar_full + st * 8, php, flag);
            const uint32_t base = sbase + st * STAGE_BYTES + krow * 128;
            float c0[4] = {0.f, 0.f, 0.f, 0.f}, c1[4] = {0.f, 0.f, 0.f, 0.f};
            uint32_t a[8][4];
#pragma unroll
            for (int ks = 0; ks < 8; ks++)
                ldsm_x4(a[ks], base + (ks >> 2) * 8192 + (((uint32_t)((ks & 3) * 2) + khi) ^ l8) * 16);
#pragma unroll
            for (int ks = 0; ks < 8; ks++) {
                if (ks & 1) mma16816(c1, a[ks], qf[ks][0], qf[ks][1]);
                else mma16816(c0, a[ks], qf[ks][0], qf[ks][1]);
            }
            __syncwarp();
            if (lane == 0) mbar_arrive_cnt(bar_empty + st * 8, 2);
#pragma unroll
            for (int e = 0; e < 4; e++) sc[i][e] = bf16r(bf16r(c0[e] + c1[e]) * 0.08838834764831845f);
            st += 2;
            if (st >= NSTAGE) { st -= NSTAGE; php ^= 1u; }
        }
        stage += 16 - NSTAGE;
        ph ^= 1u;
        if (stage >= NSTAGE) { stage -= NSTAGE; ph ^= 1u; }
    }
    {
        float m0 = sc[0][0], m1 = sc[0][1];
#pragma unroll
        for (int i = 0; i < 8; i++) {
            m0 = fmaxf(m0, fmaxf(sc[i][0], sc[i][2]));
            m1 = fmaxf(m1, fmaxf(sc[i][1], sc[i][3]));
        }
#pragma unroll
        for (int o = 4; o < 32; o <<= 1) {
            m0 = fmaxf(m0, __shfl_xor_sync(0xffffffffu, m0, o));
            m1 = fmaxf(m1, __shfl_xor_sync(0xffffffffu, m1, o));
        }
        float2* mx = reinterpret_cast<float2*>(sptr + SM_MX);
        if (g == 0) mx[warp * 4 + t] = make_float2(m0, m1);
        bar_sync(BAR_X, 288);
#pragma unroll
        for (int w = 0; w < 8; w++) {
            const float2 v = mx[w * 4 + t];
            m0 = fmaxf(m0, v.x);
            m1 = fmaxf(m1, v.y);
        }
        float l0 = 0.f, l1 = 0.f;
#pragma unroll
        for (int i = 0; i < 8; i++) {
            const float e0 = exp2f((sc[i][0] - m0) * 1.4426950408889634f);
            const float e1 = exp2f((sc[i][1] - m1) * 1.4426950408889634f);
            const float e2 = exp2f((sc[i][2] - m0) * 1.4426950408889634f);
            const float e3 = exp2f((sc[i][3] - m1) * 1.4426950408889634f);
            l0 += e0 + e2;
            l1 += e1 + e3;
            const uint32_t key = (2 * i + kh2) * 64 + mt * 16 + g;
            sts32(sbase + SM_P + key * 16 + t * 4, pack_bf16(e0, e1));
            sts32(sbase + SM_P + (key + 8) * 16 + t * 4, pack_bf16(e2, e3));
        }
#pragma unroll
        for (int o = 4; o < 32; o <<= 1) {
            l0 += __shfl_xor_sync(0xffffffffu, l0, o);
            l1 += __shfl_xor_sync(0xffffffffu, l1, o);
        }
        float2* ls = reinterpret_cast<float2*>(sptr + SM_LS);
        if (g == 0) ls[warp * 4 + t] = make_float2(l0, l1);
        bar_sync(BAR_CONS, 256);
        if (warp == 0) {
            l0 = 0.f;
            l1 = 0.f;
#pragma unroll
            for (int w = 0; w < 8; w++) {
                const float2 v = ls[w * 4 + t];
                l0 += v.x;
                l1 += v.y;
            }
            if (g == 0) st4(scr + G_ML + c * 16 + t * 4, enc(m0, tag), enc(l0, tag), enc(m1, tag), enc(l1, tag));
            bar_arrive(BAR_ML, 64);
        }
    }
    {
        float acc0[4] = {0.f, 0.f, 0.f, 0.f}, acc1[4] = {0.f, 0.f, 0.f, 0.f};
        const uint32_t paddr = sbase + SM_P + lane * 16;
        unsigned int* p = scr + G_O + ((pair * 8 + 2 * t) * 8 + (c & 7)) * 128 + warp * 16 + 2 * g;
#pragma unroll 1
        for (int j = 0; j < 16; j++) {
            if (j == PW_J) {
                st2(p, 0u, 0u);
                st2(p + 1024, 0u, 0u);
                if (t < 2) {
#pragma unroll
                    for (int e = 0; e < 4; e++) {
                        st2(scr + G_A + dst_off + e * 1024, 0u, 0u);
                        st2(scr + G_B + dst_off + e * 1024, 0u, 0u);
                    }
                }
            }
            uint32_t pb[2][4];
            ldsm_x4_t(pb[0], paddr + j * 1024);
            ldsm_x4_t(pb[1], paddr + j * 1024 + 512);
            mbar_wait(bar_full + stage * 8, ph, flag);
            const uint32_t base = sbase + stage * STAGE_BYTES + kh2 * 8192 + offT;
            uint32_t a[4][4];
#pragma unroll
            for (int ks = 0; ks < 4; ks++) ldsm_x4_t(a[ks], base + ks * 2048);
            mma16816(acc0, a[0], pb[0][0], pb[0][1]);
            mma16816(acc1, a[1], pb[0][2], pb[0][3]);
            mma16816(acc0, a[2], pb[1][0], pb[1][1]);
            mma16816(acc1, a[3], pb[1][2], pb[1][3]);
            __syncwarp();
            if (lane == 0) mbar_arrive_cnt(bar_empty + stage * 8, 1);
            if (++stage == NSTAGE) { stage = 0; ph ^= 1u; }
            if (j == 14) bar_sync(BAR_F, 288);
        }
        const float2 f = *reinterpret_cast<const float2*>(sptr + SM_F + t * 8);
        st2(p, enc((acc0[0] + acc1[0]) * f.x, tag), enc((acc0[2] + acc1[2]) * f.x, tag));
        st2(p + 1024, enc((acc0[1] + acc1[1]) * f.y, tag), enc((acc0[3] + acc1[3]) * f.y, tag));
        bar_arrive(BAR_O, 384);
    }
    const uint32_t offW0 = (warp >> 1) * 2048 + rowT + ((((uint32_t)(4 * (warp & 1) + ((lane >> 3) & 1))) ^ l8) << 4);
    const uint32_t offW1 = (warp >> 1) * 2048 + rowT + ((((uint32_t)(4 * (warp & 1) + 2 + ((lane >> 3) & 1))) ^ l8) << 4);
    {
        bar_sync(BAR_HS, 288);
        float acc0[4] = {0.f, 0.f, 0.f, 0.f}, acc1[4] = {0.f, 0.f, 0.f, 0.f};
        const uint32_t baddr = sbase + SM_HS + (g & 3) * HS_STRIDE + t * 4;
#pragma unroll 1
        for (int j = 0; j < 3; j++) {
            uint32_t b[4] = {0u, 0u, 0u, 0u};
            if (bvalid) {
#pragma unroll
                for (int e = 0; e < 4; e++) b[e] = lds32(baddr + j * 64 + e * 16);
            }
            mbar_wait(bar_full + stage * 8, ph, flag);
            const uint32_t base = sbase + stage * STAGE_BYTES;
            uint32_t a[4][4];
            ldsm_x4_t(a[0], base + offW0);
            ldsm_x4_t(a[1], base + offW1);
            ldsm_x4_t(a[2], base + 8192 + offW0);
            ldsm_x4_t(a[3], base + 8192 + offW1);
            mma16816(acc0, a[0], b[0], b[1]);
            mma16816(acc1, a[1], b[0], b[1]);
            mma16816(acc0, a[2], b[2], b[3]);
            mma16816(acc1, a[3], b[2], b[3]);
            ++stage;
        }
        {
            uint32_t b0 = 0u, b1_ = 0u;
            if (bvalid) { b0 = lds32(baddr + 192); b1_ = lds32(baddr + 208); }
            mbar_wait(bar_full + stage * 8, ph, flag);
            const uint32_t base = sbase + stage * STAGE_BYTES;
            uint32_t a[2][4];
            ldsm_x4_t(a[0], base + offW0);
            ldsm_x4_t(a[1], base + offW1);
            mma16816(acc0, a[0], b0, b1_);
            mma16816(acc1, a[1], b0, b1_);
            ++stage;
        }
        if (t < 2) {
            unsigned int* p = scr + G_B + dst_off;
            st2(p, enc(acc0[0], tag), enc(acc0[1], tag));
            st2(p + 1024, enc(acc0[2], tag), enc(acc0[3], tag));
            st2(p + 2048, enc(acc1[0], tag), enc(acc1[1], tag));
            st2(p + 3072, enc(acc1[2], tag), enc(acc1[3], tag));
        }
        bar_arrive(BAR_B, 288);
    }
    {
        bar_sync(BAR_OS, 384);
        float acc0[4] = {0.f, 0.f, 0.f, 0.f}, acc1[4] = {0.f, 0.f, 0.f, 0.f};
        const uint32_t baddr = sbase + SM_OS + (g & 3) * FR_STRIDE + t * 8;
#pragma unroll 1
        for (int j = 0; j < 4; j++) {
            uint2 b0 = make_uint2(0u, 0u), b1_ = make_uint2(0u, 0u);
            if (bvalid) { b0 = lds64(baddr + j * 64); b1_ = lds64(baddr + j * 64 + 32); }
            mbar_wait(bar_full + stage * 8, ph, flag);
            const uint32_t base = sbase + stage * STAGE_BYTES;
            uint32_t a[4][4];
            ldsm_x4_t(a[0], base + offW0);
            ldsm_x4_t(a[1], base + offW1);
            ldsm_x4_t(a[2], base + 8192 + offW0);
            ldsm_x4_t(a[3], base + 8192 + offW1);
            mma16816(acc0, a[0], b0.x, b0.y);
            mma16816(acc1, a[1], b0.x, b0.y);
            mma16816(acc0, a[2], b1_.x, b1_.y);
            mma16816(acc1, a[3], b1_.x, b1_.y);
            ++stage;
        }
        if (t < 2) {
            unsigned int* p = scr + G_A + dst_off;
            st2(p, enc(acc0[0], tag), enc(acc0[1], tag));
            st2(p + 1024, enc(acc0[2], tag), enc(acc0[3], tag));
            st2(p + 2048, enc(acc1[0], tag), enc(acc1[1], tag));
            st2(p + 3072, enc(acc1[2], tag), enc(acc1[3], tag));
        }
    }
    bar_arrive(BAR_A, 288);
}

}

namespace c6 {

constexpr int CS = 6;
constexpr int NCL = 16;
constexpr int NCTA = NCL * CS;
constexpr int NTHREADS = 416;
constexpr int NST = 11;

constexpr int SM_P = NST * STAGE_BYTES;
constexpr int SM_XS = SM_P;
constexpr int SM_YS = SM_P + 8256;
constexpr int SM_OS = SM_P;
constexpr int SM_QS = SM_P + 22528;
constexpr int SM_HS = SM_QS + 2304;
constexpr int SM_RED = SM_HS + 5248;
constexpr int SM_MX = SM_RED + 2048;
constexpr int SM_LS = SM_MX + 256;
constexpr int SM_F = SM_LS + 256;
constexpr int SM_G = SM_F + 32;
constexpr int SM_ST = SM_G + 16;
constexpr int SM_OR = SM_ST + 384;
constexpr int SM_XR = SM_OR + 6144;
constexpr int SM_BAR = SM_XR + 6144;
constexpr int SM_FLAG = SM_BAR + (2 * NST + 5) * 8;
constexpr int SM_TOTAL = SM_FLAG + 8;
constexpr int SM_ALLOC = SM_TOTAL + 1024;
constexpr int HS_STRIDE = 1312;
constexpr int OS_STRIDE = 1568;
constexpr int BAR_Y = BAR_X;
constexpr int BAR_HELP = BAR_ML;

#define CAP6 5
#define LEAD6 3
#define OG_T 28100u
#define DRY_T 10500u
#define PRE6 3
#define OG_GAP 100
#define PT6 660
constexpr uint32_t P_B = PT6 * 192;
#define PACE_L PT6
constexpr uint32_t P_L = PACE_L * 192;
constexpr uint32_t P_52 = (uint32_t)((long long)P_B * (316 - 6 * LEAD6) / (6 * (52 - LEAD6)));
constexpr uint32_t P_54 = (uint32_t)((long long)P_B * (316 - 6 * LEAD6) / (6 * (54 - LEAD6)));
#define OFF6 300

constexpr int G_EPOCH = 0;
constexpr int G_Q = G_EPOCH + 128 * 4;
constexpr int G_H = G_Q + 2 * 4 * 4096;
constexpr int G_O = G_H + 2 * 4 * 4096;
constexpr int G_TOTAL = G_O + 4 * 4096;
__device__ __align__(1024) unsigned int g_scratch[G_TOTAL];

#define KTW(w, i)
#define KTA(i)

__device__ __forceinline__ void load_b(uint2 (&b)[4], uint32_t b_addr, bool bvalid) {
#pragma unroll
    for (int ks = 0; ks < 4; ks++) b[ks] = bvalid ? lds64(b_addr + ks * 32) : make_uint2(0u, 0u);
}
__device__ __forceinline__ void st_async2(uint32_t addr, float a, float b, uint32_t bar) {
    asm volatile("st.async.weak.shared::cluster.mbarrier::complete_tx::bytes.v2.f32 [%0], {%1, %2}, [%3];"
                 ::"r"(addr), "f"(a), "f"(b), "r"(bar) : "memory");
}
__device__ __forceinline__ void st_async4(uint32_t addr, float a, float b, float c, float d, uint32_t bar) {
    asm volatile("st.async.weak.shared::cluster.mbarrier::complete_tx::bytes.v4.f32 [%0], {%1, %2, %3, %4}, [%5];"
                 ::"r"(addr), "f"(a), "f"(b), "f"(c), "f"(d), "r"(bar) : "memory");
}
__device__ __forceinline__ uint32_t mapa(uint32_t addr, uint32_t rank) {
    uint32_t r;
    asm volatile("mapa.shared::cluster.u32 %0, %1, %2;" : "=r"(r) : "r"(addr), "r"(rank));
    return r;
}

__global__ void __launch_bounds__(NTHREADS, 1)
fused_kernel(const __nv_bfloat16* __restrict__ wq, const __nv_bfloat16* __restrict__ x, unsigned int* __restrict__ scr,
             __nv_bfloat16* __restrict__ out, const __nv_bfloat16* __restrict__ gate_w, const __nv_bfloat16* __restrict__ b1,
             const __grid_constant__ TMaps maps, const __nv_bfloat16* __restrict__ b2) {
    extern __shared__ unsigned char smem_raw[];
    const uint32_t sbase = (smem_u32(smem_raw) + 1023u) & ~1023u;
    unsigned char* sptr = smem_raw + (sbase - smem_u32(smem_raw));
    volatile uint32_t* flag = reinterpret_cast<volatile uint32_t*>(sptr + SM_FLAG);

    const int c = blockIdx.x;
    const int tid = threadIdx.x;
    const int warp = tid >> 5;
    const int lane = tid & 31;
    const int cl = c / CS, r = c - cl * CS;
    const int u0 = 8 * cl + (r < 2 ? 2 * r : r + 2);
    const int v0 = 7 * cl + 2 * (r - 2);
    const int nblk = 22 - ((0x0021100 >> (4 * r)) & 3);
    const int n2 = r < 4 ? 5 : 4;
    const int w2_0 = min(5 * r, 24), wo_0 = 5 * r + (r == 5);
    const uint32_t bar_full = sbase + SM_BAR;
    const uint32_t bar_empty = sbase + SM_BAR + NST * 8;
    const uint32_t bar_st = sbase + SM_BAR + 2 * NST * 8;
    const uint32_t bar_or = bar_st + 8;
    const uint32_t bar_xr = bar_st + 24;

    KTW(0, 0);
    if (warp == 8) {
        uint32_t t0 = 0;
        if (lane == 0) {
#pragma unroll
            for (int j = 0; j < LEAD6; j++) mbar_init(bar_full + j * 8, 1);
            asm volatile("fence.mbarrier_init.release.cluster;" ::: "memory");
            asm volatile("fence.proxy.async.shared::cta;" ::: "memory");
#pragma unroll
            for (int j = 0; j < LEAD6; j++) {
                mbar_expect_tx(bar_full + j * 8, STAGE_BYTES);
                tma_3d(sbase + j * STAGE_BYTES, &maps.wq3, 0, (u0 & 1) * 512 + j * 128, u0 >> 1, bar_full + j * 8);
            }
            t0 = gtime32() + OFF6 + (r * NCL + cl) * PT6 / 128;
#pragma unroll
            for (int i = LEAD6; i < NST; i++) mbar_init(bar_full + i * 8, 1);
#pragma unroll
            for (int i = 0; i < NST; i++) mbar_init(bar_empty + i * 8, 8);
#pragma unroll
            for (int i = 0; i < 5; i++) {
                mbar_init(bar_st + i * 8, 1);
                mbar_expect_tx(bar_st + i * 8, i == 0 ? 384 : 3072);
            }
            *flag = 0u;
            asm volatile("fence.mbarrier_init.release.cluster;" ::: "memory");
            asm volatile("fence.proxy.async.shared::cta;" ::: "memory");
            prefetch_tmap(&maps.w1n);
            prefetch_tmap(&maps.k);
            prefetch_tmap(&maps.v);
            prefetch_tmap(&maps.w2n);
            prefetch_tmap(&maps.won);
        }
        __syncwarp();
        asm volatile("barrier.cluster.arrive.relaxed.aligned;" ::: "memory");
        bar_arrive(BAR_INIT, NTHREADS);
        if (lane == 0) {
#define HW 1
            const int kv_row0 = (cl / HW) * HW * SK + (r * HW + cl % HW) * 64;
            uint32_t fb = bar_full + LEAD6 * 8, eph = 1u;
            uint32_t lb = bar_full + (LEAD6 + NST - CAP6) % NST * 8, lph = 1u;
            uint32_t due = t0 << 8;
#pragma unroll 1
            for (int phase = 0; phase < 7; phase++) {
                const CUtensorMap* map;
                int row, drow = 128, blk, n;
                uint32_t per = (r == 2 || r == 3) ? P_54 : P_52;
                if (phase == 0) {
                    map = &maps.wq3; row = (u0 & 1) * 512 + LEAD6 * 128; blk = u0 >> 1; n = 4 - LEAD6;
                } else if (phase < 3) {
                    const int unit = r < 2 ? u0 + 1 : v0 + phase - 1;
                    map = r < 2 ? &maps.wq3 : &maps.w1n; row = (unit & 1) * 512; blk = unit >> 1;
                    n = (phase == 2 && (r < 2 || r == 5)) ? 0 : 4;
                } else if (phase < 5) {
                    map = phase == 3 ? &maps.k : &maps.v; row = kv_row0; drow = 384 * HW; blk = 0; n = nblk;
                } else {
                    map = phase == 5 ? &maps.w2n : &maps.won; row = (phase == 5 ? w2_0 : wo_0) * 128; blk = cl;
                    n = phase == 5 ? n2 : 10 - n2; per = P_L;
                }
#pragma unroll 1
                for (int j = 0; j < n; j++) {
                    const uint32_t dst = sbase + (fb - bar_full) * (STAGE_BYTES / 8);
                    mbar_wait(lb, lph, flag);
                    mbar_wait(fb + NST * 8, eph, flag);
                    mbar_expect_tx(fb, STAGE_BYTES);
                    for (int it = 0; it < 100000 && (int)((gtime32() << 8) - due) < 0; it++) {}
                    tma_3d(dst, map, 0, row, blk, fb);
                    row += drow;
                    if (j == 20 && r == 5) row -= 7 * 64 * HW;
                    due += per;
                    fb += 8;
                    if (fb == bar_empty) { fb = bar_full; eph ^= 1u; }
                    lb += 8;
                    if (lb == bar_empty) { lb = bar_full; lph ^= 1u; }
                }
            }
            KTW(8, 13);
        }
        return;
    }
    asm volatile("barrier.cluster.arrive.relaxed.aligned;" ::: "memory");

    const int g = lane >> 2;
    const int t = lane & 3;
    const int mt = warp & 3;
    const int kh2 = warp >> 2;
    const uint32_t epoch = ld1(scr + G_EPOCH + c * 4) + 1u;
    asm volatile("prefetch.global.L2 [%0];" ::"l"(wq + (size_t)((u0 & 1) * 512 + (tid < 256 ? tid : tid - 32)) * 4096 + (u0 >> 1) * 64));
    const uint32_t tag = 1u + epoch % 3u;

    if (warp >= 9) {
        const int hb = warp - 9;
        const uint32_t ts0 = gtime32();
        const bool fin = r < 4 && hb < 2;
        const int col = cl * 64 + r * 16 + hb * 8 + (lane & 7);
        float b2v = 0.f;
        {
            uint4 xv[4], gw[4];
#pragma unroll
            for (int i = 0; i < 4; i++) xv[i] = __ldg(reinterpret_cast<const uint4*>(x) + hb * 128 + i * 32 + lane);
#pragma unroll
            for (int i = 0; i < 4; i++) gw[i] = __ldg(reinterpret_cast<const uint4*>(gate_w) + i * 32 + lane);
            if (fin) b2v = __bfloat162float(b2[col]);
            bar_sync(BAR_INIT, NTHREADS);
            float s0 = 0.f, s1 = 0.f, zs = 0.f;
#pragma unroll
            for (int i = 0; i < 4; i++) {
                const uint32_t xa[4] = {xv[i].x, xv[i].y, xv[i].z, xv[i].w};
                const uint32_t wa[4] = {gw[i].x, gw[i].y, gw[i].z, gw[i].w};
#pragma unroll
                for (int e = 0; e < 4; e++) {
                    s0 += bf_lo(xa[e]);
                    s1 += bf_hi(xa[e]);
                    zs += bf16r(bf_lo(xa[e]) * bf_lo(wa[e]));
                    zs += bf16r(bf_hi(xa[e]) * bf_hi(wa[e]));
                }
            }
            float s = s0 + s1;
#pragma unroll
            for (int o = 16; o > 0; o >>= 1) {
                s += __shfl_xor_sync(0xffffffffu, s, o);
                zs += __shfl_xor_sync(0xffffffffu, zs, o);
            }
            if (r >= 2) {
                const float mean = s * (1.0f / 1024.0f);
                float q0 = 0.f, q1 = 0.f;
#pragma unroll
                for (int i = 0; i < 4; i++) {
                    const uint32_t xa[4] = {xv[i].x, xv[i].y, xv[i].z, xv[i].w};
#pragma unroll
                    for (int e = 0; e < 4; e++) {
                        const float d0 = bf_lo(xa[e]) - mean, d1 = bf_hi(xa[e]) - mean;
                        q0 = fmaf(d0, d0, q0);
                        q1 = fmaf(d1, d1, q1);
                    }
                }
                float q = q0 + q1;
#pragma unroll
                for (int o = 16; o > 0; o >>= 1) q += __shfl_xor_sync(0xffffffffu, q, o);
                const float mb = bf16r(mean);
                const float vb = bf16r(q * (1.0f / 1024.0f));
                const float den = bf16r(sqrtf(bf16r(vb + 1e-5f)));
#pragma unroll
                for (int i = 0; i < 4; i++) {
                    const uint32_t xa[4] = {xv[i].x, xv[i].y, xv[i].z, xv[i].w};
                    uint32_t ya[4];
#pragma unroll
                    for (int e = 0; e < 4; e++) ya[e] = pack_bf16(bf16r(bf_lo(xa[e]) - mb) / den, bf16r(bf_hi(xa[e]) - mb) / den);
                    *reinterpret_cast<uint4*>(sptr + SM_YS + hb * XS_STRIDE + (i * 32 + lane) * 16) = make_uint4(ya[0], ya[1], ya[2], ya[3]);
                }
                bar_arrive(BAR_Y, 384);
            }
            zs = bf16r(zs);
            if (lane == 0) reinterpret_cast<float*>(sptr + SM_G)[hb] = bf16r(1.0f / (1.0f + __expf(-zs)));
        }
        const int sl = r + 6 * (hb - 2);
        const bool red_o = hb >= 2 && sl < 8;
        unsigned int* const o_dst = scr + G_O + cl * 1024 + g * 128 + sl * 16 + t * 4;
#pragma unroll 1
        for (int w = 0; w < 1000 && gtime32() - ts0 < DRY_T; w++) __nanosleep(200);
#pragma unroll 1
        for (uint32_t dry = 1u; dry < 2u; dry--) {
        if (!dry) {
        bar_sync(BAR_HELP, 160);
        if (red_o) st4(o_dst, 0u, 0u, 0u, 0u);
        if (hb == 3) {
            mbar_wait_cluster(bar_st, flag);
            float4 d = make_float4(-INFINITY, 0.f, -INFINITY, 0.f);
            if (g < CS) d = *reinterpret_cast<const float4*>(sptr + SM_ST + lane * 16);
            float M0 = d.x, M1 = d.z;
#pragma unroll
            for (int o = 4; o < 32; o <<= 1) {
                M0 = fmaxf(M0, __shfl_xor_sync(0xffffffffu, M0, o));
                M1 = fmaxf(M1, __shfl_xor_sync(0xffffffffu, M1, o));
            }
            const float w0 = exp2f((d.x - M0) * 1.4426950408889634f), w1 = exp2f((d.z - M1) * 1.4426950408889634f);
            float L0 = w0 * d.y, L1 = w1 * d.w;
#pragma unroll
            for (int o = 4; o < 32; o <<= 1) {
                L0 += __shfl_xor_sync(0xffffffffu, L0, o);
                L1 += __shfl_xor_sync(0xffffffffu, L1, o);
            }
            if (g == r) *reinterpret_cast<float2*>(sptr + SM_F + t * 8) = make_float2(w0 / L0, w1 / L1);
            bar_arrive(BAR_F, 288);
        }
        {
            const unsigned int* p = scr + G_H + hb * 4096 + w2_0 * 128 + lane * 4;
            const uint32_t* pb = reinterpret_cast<const uint32_t*>(b1 + w2_0 * 128 + g * 16 + 2 * t);
#pragma unroll 1
            for (int i = 0; i < n2; i++) {
                const uint32_t ba = __ldg(pb + i * 64), bb = __ldg(pb + i * 64 + 4);
                uint4 d0, d1;
#pragma unroll 1
                for (uint32_t it = 0; it < POLL_LIMIT; it++) {
                    d0 = ld4(p + i * 128);
                    d1 = ld4(p + i * 128 + 4 * 4096);
                    if (warp_ok(bad4(d0, tag) | bad4(d1, tag))) break;
                    __nanosleep(200);
                }
                const float sv[4] = {dec(d0.x) + dec(d1.x), dec(d0.z) + dec(d1.z), dec(d0.y) + dec(d1.y), dec(d0.w) + dec(d1.w)};
                const float bv[4] = {bf_lo(ba), bf_hi(ba), bf_lo(bb), bf_hi(bb)};
                float h[4];
#pragma unroll
                for (int e = 0; e < 4; e++) {
                    const float v = bf16r(bf16r(sv[e]) + bv[e]);
                    const float inner = 0.7978845608028654f * (v + 0.044715f * v * v * v);
                    h[e] = 0.5f * v * (1.0f + tanhf(inner));
                }
                sts64(sbase + SM_HS + hb * HS_STRIDE + i * 256 + lane * 8, pack_bf16(h[0], h[1]), pack_bf16(h[2], h[3]));
            }
            KTW(9, 7);
            bar_arrive(BAR_HS, 384);
        }
        bar_sync(BAR_O, 384);
        }
        if (red_o) {
            const float4* po = reinterpret_cast<const float4*>(sptr + SM_OR + (hb - 2) * 3072) + lane;
            if (!dry) mbar_wait_cluster(bar_or + (hb - 2) * 8, flag);
            float4 v[CS];
#pragma unroll
            for (int s = 0; s < CS; s++) v[s] = po[s * 32];
            const float o0 = ((v[0].x + v[1].x) + (v[2].x + v[3].x)) + (v[4].x + v[5].x);
            const float o1 = ((v[0].y + v[1].y) + (v[2].y + v[3].y)) + (v[4].y + v[5].y);
            const float o2 = ((v[0].z + v[1].z) + (v[2].z + v[3].z)) + (v[4].z + v[5].z);
            const float o3 = ((v[0].w + v[1].w) + (v[2].w + v[3].w)) + (v[4].w + v[5].w);
            asm volatile("{\n.reg .pred p;\nsetp.eq.u32 p, %5, 0;\n@p st.relaxed.gpu.global.v4.b32 [%0], {%1, %2, %3, %4};\n}\n"
                         ::"l"(o_dst), "r"(__float_as_uint(bf16r(o0)) | tag), "r"(__float_as_uint(bf16r(o1)) | tag),
                         "r"(__float_as_uint(bf16r(o2)) | tag), "r"(__float_as_uint(bf16r(o3)) | tag), "r"(dry) : "memory");
            KTW(11, 28);
        }
        for (int w = 0; w < 100000 && gtime32() - ts0 < (dry ? 0u : OG_T); w++) {}
        {
            const unsigned int* po = scr + G_O + hb * 4096 + wo_0 * 128 + lane * 4;
            uint4 d[6];
#pragma unroll
            for (int s = 0; s < 6; s++) d[s] = make_uint4(0u, 0u, 0u, 0u);
            uint32_t pend = r < 4 ? 0x1fu : 0x3fu;
#pragma unroll 1
            for (uint32_t it = 0; it < (dry ? 1u : POLL_LIMIT); it++) {
                const uint32_t m = dry ? 0u : pend;
#pragma unroll
                for (int s = 0; s < 6; s++)
                    asm volatile("{\n.reg .pred p;\nsetp.ne.u32 p, %5, 0;\n@p ld.relaxed.gpu.global.v4.b32 {%0, %1, %2, %3}, [%4];\n}\n"
                                 : "+r"(d[s].x), "+r"(d[s].y), "+r"(d[s].z), "+r"(d[s].w) : "l"(po + s * 128), "r"(m & (1u << s)) : "memory");
#pragma unroll
                for (int s = 0; s < 6; s++) {
                    const uint32_t ok = warp_ok(bad4(d[s], tag)) ? m & (1u << s) : 0u;
                    asm volatile("{\n.reg .pred p;\nsetp.ne.u32 p, %3, 0;\n@p st.shared.v2.b32 [%0], {%1, %2};\n}\n"
                                 ::"r"(sbase + SM_OS + hb * OS_STRIDE + s * 256 + lane * 8), "r"(__byte_perm(d[s].x, d[s].z, 0x7632)),
                                 "r"(__byte_perm(d[s].y, d[s].w, 0x7632)), "r"(ok) : "memory");
                    pend ^= ok;
                }
                if (pend == 0u) {
                    break;
                }
                __nanosleep(OG_GAP);
            }
            KTA(15);
            if (!dry) bar_arrive(BAR_OS, 384);
        }
        }
        const float gate = reinterpret_cast<const float*>(sptr + SM_G)[lane >> 3];
        if (fin) {
            const float gm = bf16r(1.0f - gate);
            float term[2];
#pragma unroll
            for (int br = 0; br < 2; br++) {
                const float* xr = reinterpret_cast<const float*>(sptr + SM_XR) + br * 768 + hb * 32 + (lane & 7) * 4 + (lane >> 3);
                mbar_wait_cluster(bar_xr + br * 8, flag);
                KTW(9, 10 + br);
                float v[12];
#pragma unroll
                for (int s = 0; s < 12; s++) v[s] = xr[s * 64];
#pragma unroll
                for (int s = 0; s < 6; s++) v[s] += v[s + 6];
                const float sum = bf16r(((v[0] + v[1]) + (v[2] + v[3])) + (v[4] + v[5]));
                term[br] = br == 0 ? bf16r(gm * bf16r(sum + b2v)) : bf16r(gate * sum);
            }
            out[(lane >> 3) * D_MODEL + col] = __float2bfloat16_rn(term[1] + term[0]);
        }
        KTW(9, 12);
        return;
    }

    {
        const uint4 x0 = __ldg(reinterpret_cast<const uint4*>(x) + tid);
        const uint4 x1 = __ldg(reinterpret_cast<const uint4*>(x) + 256 + tid);
        if (t < 2 && (kh2 == 0 || r < 2)) {
            unsigned int* const q_dst = scr + G_Q + (((u0 + kh2) & 1) * 4 + 2 * t) * 4096 + (u0 >> 1) * 64 + mt * 16 + 2 * g;
            st2(q_dst, 0u, 0u);
            st2(q_dst + 4096, 0u, 0u);
        }
        *reinterpret_cast<uint4*>(sptr + SM_XS + (tid >> 7) * XS_STRIDE + (tid & 127) * 16) = x0;
        *reinterpret_cast<uint4*>(sptr + SM_XS + (2 + (tid >> 7)) * XS_STRIDE + (tid & 127) * 16) = x1;
    }
    bar_sync(BAR_INIT, NTHREADS);

    int stage = 0;
    uint32_t ph = 0;
    const uint32_t l8 = lane & 7;
    const uint32_t rowT = (l8 + 8 * (lane >> 4)) * 128;
    const uint32_t offT = rowT + ((((uint32_t)(2 * mt + ((lane >> 3) & 1))) ^ l8) << 4);
    const uint32_t aoff = sbase + kh2 * 8192 + offT;
    const bool bvalid = g < 4;

#pragma unroll 1
    for (int ui = 0; ui < ((r >= 2 && r <= 4) ? 3 : 2); ui++) {
        const bool isq = ui == 0 || r < 2;
        const int unit = isq ? u0 + ui : v0 + ui - 1;
        float4* const red = reinterpret_cast<float4*>(sptr + SM_RED) + (ui & 1) * 64 + mt * 16 + (g * 2 + (t & 1));
        unsigned int* const dst = scr + (isq ? G_Q : G_H) + ((unit & 1) * 4 + 2 * t) * 4096 + (unit >> 1) * 64 + mt * 16 + 2 * g;
        float acc0[4] = {0.f, 0.f, 0.f, 0.f}, acc1[4] = {0.f, 0.f, 0.f, 0.f};
        const uint32_t baddr = sbase + (isq ? SM_XS : SM_YS) + (g & 3) * XS_STRIDE + ((unit & 1) * 512 + kh2 * 64 + 2 * t) * 2;
        if (ui == 1 && r >= 2) bar_sync(BAR_Y, 384);
#pragma unroll 1
        for (int j = 0; j < 4; j++) {
            mbar_wait(bar_full + stage * 8, ph, flag);
            gemv_tile4(acc0, acc1, aoff + stage * STAGE_BYTES, baddr + j * 256, bvalid);
            __syncwarp();
            if (lane == 0) mbar_arrive_cnt(bar_empty + stage * 8, 1);
            if (++stage == NST) { stage = 0; ph ^= 1u; }
        }
        if (kh2 == 1 && t < 2) *red = make_float4(acc0[0] + acc1[0], acc0[1] + acc1[1], acc0[2] + acc1[2], acc0[3] + acc1[3]);
        bar_sync(BAR_PAIR + mt, 64);
        if (kh2 == 0 && t < 2) {
            const float4 o = *red;
            st2(dst, enc(acc0[0] + acc1[0] + o.x, tag), enc(acc0[2] + acc1[2] + o.z, tag));
            st2(dst + 4096, enc(acc0[1] + acc1[1] + o.y, tag), enc(acc0[3] + acc1[3] + o.w, tag));
        }
    }
    KTW(0, 1);
    mbar_wait(bar_full + stage * 8, ph, flag);
    uint32_t qf[8][2];
    {
        const unsigned int* p = scr + G_Q + cl * 1024 + tid * 4;
        uint4 d0, d1;
#pragma unroll 1
        for (uint32_t it = 0; it < POLL_LIMIT; it++) {
            d0 = ld4(p);
            d1 = ld4(p + 4 * 4096);
            if (warp_ok(bad4(d0, tag) | bad4(d1, tag))) break;
            __nanosleep(200);
        }
        sts64(sbase + SM_QS + warp * FR_STRIDE + lane * 8,
              pack_bf16(dec(d0.x) + dec(d1.x), dec(d0.z) + dec(d1.z)), pack_bf16(dec(d0.y) + dec(d1.y), dec(d0.w) + dec(d1.w)));
        bar_sync(BAR_CONS, 256);
#pragma unroll
        for (int ks = 0; ks < 8; ks++) {
            const uint2 v = lds64(sbase + SM_QS + g * FR_STRIDE + (ks * 4 + t) * 8);
            qf[ks][0] = v.x;
            qf[ks][1] = v.y;
        }
    }
    KTW(0, 2);
    {
        float sc[11][4];
        const bool full = nblk - kh2 >= 21;
        {
            int st = stage + kh2;
            uint32_t php = ph;
            if (st >= NST) { st -= NST; php ^= 1u; }
            const uint32_t krow = mt * 16 + l8 + 8 * ((lane >> 3) & 1);
            const uint32_t khi = lane >> 4;
#pragma unroll
            for (int i = 0; i < 11; i++) {
                if (i < 10 || full) {
                    mbar_wait(bar_full + st * 8, php, flag);
                    const uint32_t base = sbase + st * STAGE_BYTES + krow * 128;
                    float c0[4] = {0.f, 0.f, 0.f, 0.f}, c1[4] = {0.f, 0.f, 0.f, 0.f};
                    uint32_t a[8][4];
#pragma unroll
                    for (int ks = 0; ks < 8; ks++)
                        ldsm_x4(a[ks], base + (ks >> 2) * 8192 + (((uint32_t)((ks & 3) * 2) + khi) ^ l8) * 16);
#pragma unroll
                    for (int ks = 0; ks < 8; ks++) {
                        if (ks & 1) mma16816(c1, a[ks], qf[ks][0], qf[ks][1]);
                        else mma16816(c0, a[ks], qf[ks][0], qf[ks][1]);
                    }
                    __syncwarp();
                    if (lane == 0) mbar_arrive_cnt(bar_empty + st * 8, 2);
#pragma unroll
                    for (int e = 0; e < 4; e++) sc[i][e] = bf16r(bf16r(c0[e] + c1[e]) * 0.08838834764831845f);
                    st += 2;
                    if (st >= NST) { st -= NST; php ^= 1u; }
                } else {
#pragma unroll
                    for (int e = 0; e < 4; e++) sc[i][e] = sc[0][e];
                }
            }
            stage += nblk - NST;
            ph ^= 1u;
            if (stage >= NST) { stage -= NST; ph ^= 1u; }
        }
        KTW(0, 3);
        float m0 = sc[0][0], m1 = sc[0][1];
#pragma unroll
        for (int i = 0; i < 11; i++) {
            m0 = fmaxf(m0, fmaxf(sc[i][0], sc[i][2]));
            m1 = fmaxf(m1, fmaxf(sc[i][1], sc[i][3]));
        }
#pragma unroll
        for (int o = 4; o < 32; o <<= 1) {
            m0 = fmaxf(m0, __shfl_xor_sync(0xffffffffu, m0, o));
            m1 = fmaxf(m1, __shfl_xor_sync(0xffffffffu, m1, o));
        }
        float2* mx = reinterpret_cast<float2*>(sptr + SM_MX);
        if (g == 0) mx[warp * 4 + t] = make_float2(m0, m1);
        bar_sync(BAR_CONS, 256);
#pragma unroll
        for (int w = 0; w < 8; w++) {
            const float2 v = mx[w * 4 + t];
            m0 = fmaxf(m0, v.x);
            m1 = fmaxf(m1, v.y);
        }
        float l0 = 0.f, l1 = 0.f;
#pragma unroll
        for (int i = 0; i < 11; i++) {
            if (i < 10 || full) {
                const float e0 = exp2f((sc[i][0] - m0) * 1.4426950408889634f);
                const float e1 = exp2f((sc[i][1] - m1) * 1.4426950408889634f);
                const float e2 = exp2f((sc[i][2] - m0) * 1.4426950408889634f);
                const float e3 = exp2f((sc[i][3] - m1) * 1.4426950408889634f);
                l0 += e0 + e2;
                l1 += e1 + e3;
                const uint32_t key = (2 * i + kh2) * 64 + mt * 16 + g;
                sts32(sbase + SM_P + key * 16 + t * 4, pack_bf16(e0, e1));
                sts32(sbase + SM_P + (key + 8) * 16 + t * 4, pack_bf16(e2, e3));
            }
        }
#pragma unroll
        for (int o = 4; o < 32; o <<= 1) {
            l0 += __shfl_xor_sync(0xffffffffu, l0, o);
            l1 += __shfl_xor_sync(0xffffffffu, l1, o);
        }
        float2* ls = reinterpret_cast<float2*>(sptr + SM_LS);
        if (g == 0) ls[warp * 4 + t] = make_float2(l0, l1);
        bar_sync(BAR_CONS, 256);
        asm volatile("barrier.cluster.wait.acquire.aligned;" ::: "memory");
        if (warp == 0) {
            l0 = 0.f;
            l1 = 0.f;
#pragma unroll
            for (int w = 0; w < 8; w++) {
                const float2 v = ls[w * 4 + t];
                l0 += v.x;
                l1 += v.y;
            }
            if (g < CS) st_async4(mapa(sbase + SM_ST + r * 64 + t * 16, g), m0, l0, m1, l1, mapa(bar_st, g));
            bar_arrive(BAR_HELP, 160);
        }
    }
    {
        float acc0[4] = {0.f, 0.f, 0.f, 0.f}, acc1[4] = {0.f, 0.f, 0.f, 0.f};
        const uint32_t paddr = sbase + SM_P + lane * 16;
        const uint32_t sel = warp >= CS ? 1u : 0u;
        const uint32_t ro = mapa(sbase + SM_OR + sel * 3072 + r * 512 + t * 128 + g * 8, warp - sel * CS);
        const uint32_t rb = mapa(bar_or + sel * 8, warp - sel * CS);
#pragma unroll 1
        for (int j = 0; j < nblk; j++) {
            uint32_t pb[2][4];
            ldsm_x4_t(pb[0], paddr + j * 1024);
            ldsm_x4_t(pb[1], paddr + j * 1024 + 512);
            mbar_wait(bar_full + stage * 8, ph, flag);
            const uint32_t base = aoff + stage * STAGE_BYTES;
            uint32_t a[4][4];
#pragma unroll
            for (int ks = 0; ks < 4; ks++) ldsm_x4_t(a[ks], base + ks * 2048);
            mma16816(acc0, a[0], pb[0][0], pb[0][1]);
            mma16816(acc1, a[1], pb[0][2], pb[0][3]);
            mma16816(acc0, a[2], pb[1][0], pb[1][1]);
            mma16816(acc1, a[3], pb[1][2], pb[1][3]);
            __syncwarp();
            if (lane == 0) mbar_arrive_cnt(bar_empty + stage * 8, 1);
            if (++stage == NST) { stage = 0; ph ^= 1u; }
            if (j == nblk - 2) {
                bar_sync(BAR_F, 288);
                bar_sync(BAR_HS, 384);
            }
        }
        const float2 f = *reinterpret_cast<const float2*>(sptr + SM_F + t * 8);
        st_async2(ro, (acc0[0] + acc1[0]) * f.x, (acc0[2] + acc1[2]) * f.x, rb);
        st_async2(ro + 64, (acc0[1] + acc1[1]) * f.y, (acc0[3] + acc1[3]) * f.y, rb);
        bar_arrive(BAR_O, 384);
    }
    KTW(0, 4);
    const uint32_t ra = mapa(sbase + SM_XR + (r * 2 + kh2) * 256 + g * 16 + (t & 1) * 8, mt);
    const uint32_t rb = mapa(bar_xr, mt);
    uint32_t baddr = sbase + SM_HS + (g & 3) * HS_STRIDE + t * 8 + kh2 * 128;
#pragma unroll 1
    for (int br = 0; br < 2; br++) {
        float acc[4][4];
#pragma unroll
        for (int m = 0; m < 4; m++) acc[m][0] = acc[m][1] = acc[m][2] = acc[m][3] = 0.f;
        const int n = br == 0 ? n2 : 10 - n2;
        {
            uint32_t pa[PRE6][4][4];
#pragma unroll
            for (int j = 0; j < PRE6; j++) {
                mbar_wait(bar_full + stage * 8, ph, flag);
#pragma unroll
                for (int ks = 0; ks < 4; ks++) ldsm_x4_t(pa[j][ks], aoff + stage * STAGE_BYTES + ks * 2048);
                if (++stage == NST) { stage = 0; ph ^= 1u; }
            }
            if (br == 1) bar_sync(BAR_OS, 384);
#pragma unroll
            for (int j = 0; j < PRE6; j++) {
                uint2 b[4];
                load_b(b, baddr + j * 256, bvalid);
#pragma unroll
                for (int ks = 0; ks < 4; ks++) mma16816(acc[ks], pa[j][ks], b[ks].x, b[ks].y);
            }
        }
#pragma unroll 1
        for (int j = PRE6; j < n; j++) {
            uint2 b[4];
            load_b(b, baddr + j * 256, bvalid);
            mbar_wait(bar_full + stage * 8, ph, flag);
            uint32_t a[4][4];
#pragma unroll
            for (int ks = 0; ks < 4; ks++) ldsm_x4_t(a[ks], aoff + stage * STAGE_BYTES + ks * 2048);
#pragma unroll
            for (int ks = 0; ks < 4; ks++) mma16816(acc[ks], a[ks], b[ks].x, b[ks].y);
            if (++stage == NST) { stage = 0; ph ^= 1u; }
        }
        if (t < 2) {
            st_async2(ra + br * 3072, (acc[0][0] + acc[1][0]) + (acc[2][0] + acc[3][0]), (acc[0][1] + acc[1][1]) + (acc[2][1] + acc[3][1]), rb + br * 8);
            st_async2(ra + br * 3072 + 128, (acc[0][2] + acc[1][2]) + (acc[2][2] + acc[3][2]), (acc[0][3] + acc[1][3]) + (acc[2][3] + acc[3][3]), rb + br * 8);
        }
        if (br == 0) {
            KTW(0, 5);
            baddr = sbase + SM_OS + (g & 3) * OS_STRIDE + t * 8 + kh2 * 128;
        }
    }
    if (tid == 0) *reinterpret_cast<volatile unsigned int*>(scr + G_EPOCH + c * 4) = epoch;
}

}
typedef CUresult (*EncodeFn)(CUtensorMap*, CUtensorMapDataType, cuuint32_t, void*, const cuuint64_t*, const cuuint64_t*,
                             const cuuint32_t*, const cuuint32_t*, CUtensorMapInterleave, CUtensorMapSwizzle,
                             CUtensorMapL2promotion, CUtensorMapFloatOOBfill);

void make_2d(EncodeFn enc_fn, CUtensorMap* tm, void* base, uint64_t cols, uint64_t rows, uint32_t box_rows) {
    cuuint64_t gd[2] = {cols, rows};
    cuuint64_t gs[1] = {cols * 2};
    cuuint32_t bd[2] = {64, box_rows};
    cuuint32_t es[2] = {1, 1};
    enc_fn(tm, CU_TENSOR_MAP_DATA_TYPE_BFLOAT16, 2, base, gd, gs, bd, es, CU_TENSOR_MAP_INTERLEAVE_NONE,
           CU_TENSOR_MAP_SWIZZLE_128B, CU_TENSOR_MAP_L2_PROMOTION_L2_128B, CU_TENSOR_MAP_FLOAT_OOB_FILL_NONE);
}
#define PROMO_KV CU_TENSOR_MAP_L2_PROMOTION_L2_256B
#define PROMO_W CU_TENSOR_MAP_L2_PROMOTION_L2_128B
void make_3d(EncodeFn enc_fn, CUtensorMap* tm, void* base, uint64_t cols, uint64_t rows, uint32_t box_rows, uint32_t box_blocks,
             CUtensorMapL2promotion promo = CU_TENSOR_MAP_L2_PROMOTION_L2_128B) {
    cuuint64_t gd[3] = {64, rows, cols / 64};
    cuuint64_t gs[2] = {cols * 2, 128};
    cuuint32_t bd[3] = {64, box_rows, box_blocks};
    cuuint32_t es[3] = {1, 1, 1};
    enc_fn(tm, CU_TENSOR_MAP_DATA_TYPE_BFLOAT16, 3, base, gd, gs, bd, es, CU_TENSOR_MAP_INTERLEAVE_NONE,
           CU_TENSOR_MAP_SWIZZLE_128B, promo, CU_TENSOR_MAP_FLOAT_OOB_FILL_NONE);
}

}

extern "C" void kernel_launch(void* const* d_in, const int* in_sizes, int n_in, void* d_out, int out_size) {
    (void)in_sizes; (void)n_in; (void)out_size;
    static TMaps maps;
    static void* cached[6] = {nullptr, nullptr, nullptr, nullptr, nullptr, nullptr};
    static EncodeFn enc_fn = nullptr;
    static void* scr = nullptr;
    static bool use_c6 = false;
    cudaLaunchConfig_t cfg = {};
    cudaLaunchAttribute at[1];
    cfg.gridDim = dim3(c6::NCTA);
    cfg.blockDim = dim3(c6::NTHREADS);
    cfg.dynamicSmemBytes = c6::SM_ALLOC;
    cfg.stream = cudaStreamPerThread;
    at[0].id = cudaLaunchAttributeClusterDimension;
    at[0].val.clusterDim.x = c6::CS;
    at[0].val.clusterDim.y = 1;
    at[0].val.clusterDim.z = 1;
    cfg.attrs = at;
    cfg.numAttrs = 1;
    if (!enc_fn) {
        void* fn = nullptr;
        cudaDriverEntryPointQueryResult qr;
        cudaGetDriverEntryPoint("cuTensorMapEncodeTiled", &fn, cudaEnableDefault, &qr);
        enc_fn = (EncodeFn)fn;
        cudaFuncSetAttribute(fb::fused_kernel, cudaFuncAttributeMaxDynamicSharedMemorySize, fb::SM_ALLOC);
        cudaFuncSetAttribute(c6::fused_kernel, cudaFuncAttributeMaxDynamicSharedMemorySize, c6::SM_ALLOC);
        int ncl = 0;
        if (cudaOccupancyMaxActiveClusters(&ncl, c6::fused_kernel, &cfg) != cudaSuccess) { ncl = 0; (void)cudaGetLastError(); }
        use_c6 = ncl >= c6::NCL;
        if (use_c6) cudaGetSymbolAddress(&scr, c6::g_scratch);
        else cudaGetSymbolAddress(&scr, fb::g_scratch);
    }
    void* cur[6] = {d_in[3], d_in[6], d_in[1], d_in[2], d_in[8], d_in[4]};
    bool same = true;
    for (int i = 0; i < 6; i++) same = same && (cur[i] == cached[i]);
    if (!same) {
        make_2d(enc_fn, &maps.wq, d_in[3], 4096, 1024, 128);
        make_2d(enc_fn, &maps.w1, d_in[6], F_DIM, 1024, 128);
        make_3d(enc_fn, &maps.k, d_in[1], 128, 16 * SK, 64, 2, PROMO_KV);
        make_3d(enc_fn, &maps.v, d_in[2], 128, 16 * SK, 64, 2, PROMO_KV);
        make_3d(enc_fn, &maps.w2, d_in[8], 1024, F_DIM, 16, 4);
        make_3d(enc_fn, &maps.wo, d_in[4], 1024, 4096, 16, 4);
        make_3d(enc_fn, &maps.w2n, d_in[8], 1024, F_DIM, 128, 1, PROMO_W);
        make_3d(enc_fn, &maps.wq3, d_in[3], 4096, 1024, 128, 1, PROMO_W);
        make_3d(enc_fn, &maps.won, d_in[4], 1024, 4096, 128, 1, PROMO_W);
        make_3d(enc_fn, &maps.w1n, d_in[6], F_DIM, 1024, 128, 1, PROMO_W);
        for (int i = 0; i < 6; i++) cached[i] = cur[i];
    }
    if (use_c6) {
        cudaLaunchKernelEx(&cfg, c6::fused_kernel, (const __nv_bfloat16*)d_in[3], (const __nv_bfloat16*)d_in[0],
                           (unsigned int*)scr, (__nv_bfloat16*)d_out, (const __nv_bfloat16*)d_in[10],
                           (const __nv_bfloat16*)d_in[7], maps, (const __nv_bfloat16*)d_in[9]);
    } else {
        fb::fused_kernel<<<fb::NCTA, fb::NTHREADS, fb::SM_ALLOC, cudaStreamPerThread>>>(
            (const __nv_bfloat16*)d_in[3], (const __nv_bfloat16*)d_in[0], (unsigned int*)scr, (__nv_bfloat16*)d_out,
            (const __nv_bfloat16*)d_in[10], (const __nv_bfloat16*)d_in[7], maps, (const __nv_bfloat16*)d_in[9]);
    }
}
```
